```python
import torch

def _softmax(x, axis=-1):
    return torch.softmax(x, dim=axis)
def _gelu(x):
    return torch.nn.functional.gelu(x, approximate="tanh")
def _silu(x):
    return torch.nn.functional.silu(x)
def _sigmoid(x):
    return torch.sigmoid(x)
def _layernorm(x, axis=-1, eps=1e-5):
    m = x.mean(dim=axis, keepdim=True)
    v = x.var(dim=axis, keepdim=True, unbiased=False)
    return (x - m) / torch.sqrt(v + eps)
def _scatter_add(tgt, idx, src, axis=0):
    return tgt.clone().index_add_(axis, idx, src)
def _segment_sum(src, seg, n):
    out = torch.zeros((n,) + src.shape[1:], dtype=src.dtype)
    return out.index_add_(0, seg, src)
def _pad(x, pw):
    flat = tuple(v for pair in reversed(pw) for v in pair)
    return torch.nn.functional.pad(x, flat)

kernel_name = 'parallel_sum__compressed_kv_cla__dense_activation_relu__prompt'

def setup_inputs():

    _w = (lambda a: (lambda t: t.to(torch.bfloat16) if t.is_floating_point() else t)(torch.as_tensor(a)))
    def _A_setup():
        B, H, Sq, Sk, D, M = 1, 32, 2048, 2048, 128, 512
        Dc = 4 * D
        return {
            "x": _w((lambda *s: torch.randn(*s, dtype=torch.bfloat16) * 0.05)(B, Sq, M)),
            "c_kv": _w((lambda *s: torch.randn(*s, dtype=torch.bfloat16) * 1.6)(B, Sk, Dc)),
            "w_q": _w((lambda *s: torch.randn(*s, dtype=torch.bfloat16) * 0.8)(M, H, D) * (M ** -0.5)),
            "w_uk": _w((lambda *s: torch.randn(*s, dtype=torch.bfloat16) * 0.8)(Dc, H, D) * (Dc ** -0.5)),
            "w_uv": _w((lambda *s: torch.randn(*s, dtype=torch.bfloat16) * 1.6)(Dc, H, D) * (Dc ** -0.5)),
            "w_o": _w((lambda *s: torch.randn(*s, dtype=torch.bfloat16) * 1.6)(H, D, M) * ((H * D) ** -0.5)),
        }
    _A_in = _A_setup()

    def _B_setup():
        B, S, D, Dff = 1, 2048, 512, 1792
        return {
            "x": _w((lambda *s: torch.randn(*s, dtype=torch.bfloat16) * 0.05)(B, S, D)),
            "w1": _w((lambda *s: torch.randn(*s, dtype=torch.bfloat16) * 0.05)(D, Dff)),
            "w2": _w((lambda *s: torch.randn(*s, dtype=torch.bfloat16) * 0.05)(Dff, D)),
        }
    _B_in = _B_setup()

    return {
        "A_x": _A_in["x"],
        "A_c_kv": _A_in["c_kv"],
        "A_w_q": _A_in["w_q"],
        "A_w_uk": _A_in["w_uk"],
        "A_w_uv": _A_in["w_uv"],
        "A_w_o": _A_in["w_o"],
        "B_x": _B_in["x"],
        "B_w1": _B_in["w1"],
        "B_w2": _B_in["w2"],
    }

def reference(A_x, A_c_kv, A_w_q, A_w_uk, A_w_uv, A_w_o, B_x, B_w1, B_w2):
    def _A_ref(x, c_kv, w_q, w_uk, w_uv, w_o):
        B, Sq, M = x.shape[0], x.shape[1], x.shape[2]
        Sk = c_kv.shape[1]
        H, D = w_q.shape[1], w_q.shape[2]
        q = torch.einsum("bqm,mhd->bhqd", x, w_q)
        k = torch.einsum("bkc,chd->bhkd", c_kv, w_uk)
        v = torch.einsum("bkc,chd->bhkd", c_kv, w_uv)
        scores = torch.einsum("bhqd,bhkd->bhqk", q, k) * (D ** -0.5)
        off = Sk - Sq
        qi = torch.arange(Sq)[:, None]
        kj = torch.arange(Sk)[None, :]
        cmask = kj <= (qi + off)
        scores = torch.where(cmask[None, None], scores, -1e9)
        p = _softmax(scores, axis=-1)
        ctx = torch.einsum("bhqk,bhkd->bhqd", p, v)
        return torch.einsum("bhqd,hdm->bqm", ctx, w_o)

    def _B_ref(x, w1, w2):
        h = torch.einsum("bsd,df->bsf", x, w1)
        zero = torch.zeros_like(h)
        h = torch.maximum(h, zero)
        return torch.einsum("bsf,fd->bsd", h, w2)

    x = A_x
    xn = _layernorm(x, axis=-1)
    return x + _A_ref(xn, A_c_kv, A_w_q, A_w_uk, A_w_uv, A_w_o) + _B_ref(xn, B_w1, B_w2)
```

```cpp
#include <cuda_runtime.h>
#include <cuda_bf16.h>
#include <cuda.h>
#include <stdint.h>

namespace {

constexpr int SEQ = 2048, DM = 512, NH = 32, DFF = 1792;
constexpr int NT = 16;
constexpr int NFB = DFF / 128;
constexpr int TILE_B = 32768, HALF_B = 16384;

__device__ __align__(1024) uint8_t g_xn[NT * 4 * TILE_B];
__device__ __align__(1024) uint8_t g_q[NH * NT * TILE_B];
__device__ __align__(1024) uint8_t g_k[NH * NT * TILE_B];
__device__ __align__(1024) uint8_t g_v[NH * NT * TILE_B];
__device__ __align__(1024) uint8_t g_h[NT * NFB * TILE_B];
constexpr int F_LN = 0, F_QA = 16, F_QB = 24, F_H = 32, F_CTX = 48, F_TICKET = 112, F_NUM = 113;
__device__ unsigned g_flag[F_NUM * 32];

__device__ __forceinline__ uint32_t smem_u32(const void* p) { return (uint32_t)__cvta_generic_to_shared(p); }
__device__ __forceinline__ void cluster_arrive() { asm volatile("barrier.cluster.arrive.relaxed.aligned;" ::: "memory"); }
__device__ __forceinline__ void cluster_wait() { asm volatile("barrier.cluster.wait.aligned;" ::: "memory"); }
__device__ __forceinline__ void prefetch_tm(const CUtensorMap* tm) { asm volatile("prefetch.tensormap [%0];" ::"l"(tm) : "memory"); }
__device__ __forceinline__ void prefetch_l2(const void* p, int bytes) {
  asm volatile("cp.async.bulk.prefetch.L2.global [%0], %1;" ::"l"(p), "r"(bytes) : "memory");
}
__device__ __forceinline__ void mbar_init(uint32_t bar, int cnt) {
  asm volatile("mbarrier.init.shared.b64 [%0], %1;" ::"r"(bar), "r"(cnt));
}
__device__ __forceinline__ void mbar_expect(uint32_t bar, int bytes) {
  asm volatile("mbarrier.arrive.expect_tx.shared.b64 _, [%0], %1;" ::"r"(bar), "r"(bytes) : "memory");
}
__device__ __forceinline__ void mbar_wait(uint32_t bar, uint32_t parity) {
  asm volatile("{\n.reg .pred p;\n.reg .u32 c;\nmov.u32 c, 0;\n"
               "WL%=:\nmbarrier.try_wait.parity.shared.b64 p, [%0], %1;\n@p bra WD%=;\n"
               "add.u32 c, c, 1;\nsetp.lt.u32 p, c, 0x1000000;\n@p bra WL%=;\ntrap;\nWD%=:\n}"
               ::"r"(bar), "r"(parity) : "memory");
}
__device__ __forceinline__ uint32_t mbar_test(uint32_t bar, uint32_t parity) {
  uint32_t ok;
  asm volatile("{\n.reg .pred p;\nmbarrier.test_wait.parity.shared.b64 p, [%1], %2;\nselp.u32 %0, 1, 0, p;\n}"
               : "=r"(ok) : "r"(bar), "r"(parity) : "memory");
  return ok;
}
__device__ __forceinline__ void mbar_arrive_cta(uint32_t bar, uint32_t cta) {
  asm volatile("{\n.reg .b32 ra;\nmapa.shared::cluster.u32 ra, %0, %1;\nmbarrier.arrive.shared::cluster.b64 _, [ra];\n}"
               ::"r"(bar), "r"(cta) : "memory");
}
__device__ __forceinline__ void bulk_load(uint32_t dst, const void* src, int bytes, uint32_t bar) {
  asm volatile("cp.async.bulk.shared::cluster.global.mbarrier::complete_tx::bytes [%0], [%1], %2, [%3];"
               ::"r"(dst), "l"(src), "r"(bytes), "r"(bar) : "memory");
}
__device__ __forceinline__ void bulk_load_mc(uint32_t dst, const void* src, int bytes, uint32_t bar) {
  asm volatile("cp.async.bulk.shared::cluster.global.mbarrier::complete_tx::bytes.multicast::cluster [%0], [%1], %2, [%3], %4;"
               ::"r"(dst), "l"(src), "r"(bytes), "r"(bar), "h"((uint16_t)3) : "memory");
}
__device__ __forceinline__ void tma_load(uint32_t dst, const CUtensorMap* tm, int c0, int c1, uint32_t bar) {
  asm volatile("cp.async.bulk.tensor.2d.shared::cluster.global.mbarrier::complete_tx::bytes [%0], [%1, {%3, %4}], [%2];"
               ::"r"(dst), "l"(tm), "r"(bar), "r"(c0), "r"(c1) : "memory");
}
__device__ __forceinline__ void tma_load_mc(uint32_t dst, const CUtensorMap* tm, int c0, int c1, uint32_t bar) {
  asm volatile("cp.async.bulk.tensor.2d.shared::cluster.global.mbarrier::complete_tx::bytes.multicast::cluster [%0], [%1, {%3, %4}], [%2], %5;"
               ::"r"(dst), "l"(tm), "r"(bar), "r"(c0), "r"(c1), "h"((uint16_t)3) : "memory");
}
__device__ __forceinline__ uint64_t policy_ef() {
  uint64_t p;
  asm volatile("createpolicy.fractional.L2::evict_first.b64 %0, 1.0;" : "=l"(p));
  return p;
}
__device__ __forceinline__ void bulk_load_ef(uint32_t dst, const void* src, int bytes, uint32_t bar, uint64_t pol) {
  asm volatile("cp.async.bulk.shared::cluster.global.mbarrier::complete_tx::bytes.L2::cache_hint [%0], [%1], %2, [%3], %4;"
               ::"r"(dst), "l"(src), "r"(bytes), "r"(bar), "l"(pol) : "memory");
}
__device__ __forceinline__ void bulk_load_mc_p(uint32_t dst, const void* src, int bytes, uint32_t bar, uint64_t pol) {
  asm volatile("cp.async.bulk.shared::cluster.global.mbarrier::complete_tx::bytes.multicast::cluster.L2::cache_hint [%0], [%1], %2, [%3], %4, %5;"
               ::"r"(dst), "l"(src), "r"(bytes), "r"(bar), "h"((uint16_t)3), "l"(pol) : "memory");
}
__device__ __forceinline__ void tma_load_ef(uint32_t dst, const CUtensorMap* tm, int c0, int c1, uint32_t bar, uint64_t pol) {
  asm volatile("cp.async.bulk.tensor.2d.shared::cluster.global.mbarrier::complete_tx::bytes.L2::cache_hint [%0], [%1, {%3, %4}], [%2], %5;"
               ::"r"(dst), "l"(tm), "r"(bar), "r"(c0), "r"(c1), "l"(pol) : "memory");
}
__device__ __forceinline__ void tma_load_mc_ef(uint32_t dst, const CUtensorMap* tm, int c0, int c1, uint32_t bar, uint64_t pol) {
  asm volatile("cp.async.bulk.tensor.2d.shared::cluster.global.mbarrier::complete_tx::bytes.multicast::cluster.L2::cache_hint [%0], [%1, {%3, %4}], [%2], %5, %6;"
               ::"r"(dst), "l"(tm), "r"(bar), "r"(c0), "r"(c1), "h"((uint16_t)3), "l"(pol) : "memory");
}
__device__ __forceinline__ void tma_reduce_add(const CUtensorMap* tm, int c0, int c1, uint32_t src) {
  asm volatile("cp.reduce.async.bulk.tensor.2d.global.shared::cta.add.tile.bulk_group [%0, {%2, %3}], [%1];"
               ::"l"(tm), "r"(src), "r"(c0), "r"(c1) : "memory");
}
__device__ __forceinline__ void stsm_x4(uint32_t addr, uint32_t r0, uint32_t r1, uint32_t r2, uint32_t r3) {
  asm volatile("stmatrix.sync.aligned.m8n8.x4.shared.b16 [%0], {%1,%2,%3,%4};" ::"r"(addr), "r"(r0), "r"(r1), "r"(r2), "r"(r3) : "memory");
}
__device__ __forceinline__ void named_sync(int id, int n) { asm volatile("bar.sync %0, %1;" ::"r"(id), "r"(n) : "memory"); }
__device__ __forceinline__ void named_arrive(int id, int n) { asm volatile("bar.arrive %0, %1;" ::"r"(id), "r"(n) : "memory"); }
__device__ __forceinline__ void wg_fence() { asm volatile("wgmma.fence.sync.aligned;" ::: "memory"); }
__device__ __forceinline__ void wg_commit() { asm volatile("wgmma.commit_group.sync.aligned;" ::: "memory"); }
template <int N> __device__ __forceinline__ void wg_wait() { asm volatile("wgmma.wait_group.sync.aligned %0;" ::"n"(N) : "memory"); }
template <int N> __device__ __forceinline__ void reg_inc() { asm volatile("setmaxnreg.inc.sync.aligned.u32 %0;" ::"n"(N)); }
template <int N> __device__ __forceinline__ void reg_dec() { asm volatile("setmaxnreg.dec.sync.aligned.u32 %0;" ::"n"(N)); }
template <int NR> __device__ __forceinline__ void fence_regs(float (&d)[NR]) {
#pragma unroll
  for (int i = 0; i < NR; i++) asm volatile("" : "+f"(d[i])::"memory");
}
template <int NR> __device__ __forceinline__ void fence_regs(uint32_t (&d)[NR]) {
#pragma unroll
  for (int i = 0; i < NR; i++) asm volatile("" : "+r"(d[i])::"memory");
}
__device__ __forceinline__ uint32_t pack_bf16(float lo, float hi) {
  uint32_t r;
  asm("cvt.rn.bf16x2.f32 %0, %1, %2;" : "=r"(r) : "f"(hi), "f"(lo));
  return r;
}
__device__ __forceinline__ uint32_t pack_bf16_relu(float lo, float hi) {
  uint32_t r;
  asm("cvt.rn.relu.bf16x2.f32 %0, %1, %2;" : "=r"(r) : "f"(hi), "f"(lo));
  return r;
}
__device__ __forceinline__ float ex2(float x) { float y; asm("ex2.approx.ftz.f32 %0, %1;" : "=f"(y) : "f"(x)); return y; }
__device__ __forceinline__ float bf16r(float x) { return __bfloat162float(__float2bfloat16_rn(x)); }
__device__ __forceinline__ void red_release(unsigned* p, unsigned v) {
  asm volatile("red.release.gpu.global.add.u32 [%0], %1;" ::"l"(p), "r"(v) : "memory");
}
__device__ __forceinline__ void red_relaxed(unsigned* p, unsigned v) {
  asm volatile("red.relaxed.gpu.global.add.u32 [%0], %1;" ::"l"(p), "r"(v) : "memory");
}
__device__ __forceinline__ void mbar_arrive(uint32_t bar) {
  asm volatile("mbarrier.arrive.shared.b64 _, [%0];" ::"r"(bar) : "memory");
}
__device__ __forceinline__ void spin_ge(const unsigned* p, unsigned target) {
  asm volatile("{\n.reg .pred p;\n.reg .u32 c, v;\nmov.u32 c, 0;\n"
               "SL%=:\nld.acquire.gpu.global.u32 v, [%0];\nsub.u32 v, v, %1;\nsetp.ge.s32 p, v, 0;\n@p bra SD%=;\n"
               "nanosleep.u32 20;\nadd.u32 c, c, 1;\nsetp.lt.u32 p, c, 0x400000;\n@p bra SL%=;\ntrap;\nSD%=:\n}"
               ::"l"(p), "r"(target) : "memory");
}

template<int TB, int NR>
__device__ __forceinline__ void wgmma_rs_n128_p(float (&d)[NR], uint32_t a0, uint32_t a1, uint32_t a2, uint32_t a3, uint64_t descB, int scaleD, int en) {
  asm volatile("{\n.reg .pred p, e;\nsetp.ne.b32 p, %69, 0;\nsetp.ne.b32 e, %71, 0;\n"
    "@e wgmma.mma_async.sync.aligned.m64n128k16.f32.bf16.bf16 {%0, %1, %2, %3, %4, %5, %6, %7, %8, %9, %10, %11, %12, %13, %14, %15, %16, %17, %18, %19, %20, %21, %22, %23, %24, %25, %26, %27, %28, %29, %30, %31, %32, %33, %34, %35, %36, %37, %38, %39, %40, %41, %42, %43, %44, %45, %46, %47, %48, %49, %50, %51, %52, %53, %54, %55, %56, %57, %58, %59, %60, %61, %62, %63}, {%64, %65, %66, %67}, %68, p, 1, 1, %70;\n}\n"
    : "+f"(d[0]), "+f"(d[1]), "+f"(d[2]), "+f"(d[3]), "+f"(d[4]), "+f"(d[5]), "+f"(d[6]), "+f"(d[7]), "+f"(d[8]), "+f"(d[9]), "+f"(d[10]), "+f"(d[11]), "+f"(d[12]), "+f"(d[13]), "+f"(d[14]), "+f"(d[15]), "+f"(d[16]), "+f"(d[17]), "+f"(d[18]), "+f"(d[19]), "+f"(d[20]), "+f"(d[21]), "+f"(d[22]), "+f"(d[23]), "+f"(d[24]), "+f"(d[25]), "+f"(d[26]), "+f"(d[27]), "+f"(d[28]), "+f"(d[29]), "+f"(d[30]), "+f"(d[31]), "+f"(d[32]), "+f"(d[33]), "+f"(d[34]), "+f"(d[35]), "+f"(d[36]), "+f"(d[37]), "+f"(d[38]), "+f"(d[39]), "+f"(d[40]), "+f"(d[41]), "+f"(d[42]), "+f"(d[43]), "+f"(d[44]), "+f"(d[45]), "+f"(d[46]), "+f"(d[47]), "+f"(d[48]), "+f"(d[49]), "+f"(d[50]), "+f"(d[51]), "+f"(d[52]), "+f"(d[53]), "+f"(d[54]), "+f"(d[55]), "+f"(d[56]), "+f"(d[57]), "+f"(d[58]), "+f"(d[59]), "+f"(d[60]), "+f"(d[61]), "+f"(d[62]), "+f"(d[63])
    : "r"(a0), "r"(a1), "r"(a2), "r"(a3), "l"(descB), "r"(scaleD), "n"(TB), "r"(en));
}
template<int TB, int NR>
__device__ __forceinline__ void wgmma_rs_n64_p(float (&d)[NR], uint32_t a0, uint32_t a1, uint32_t a2, uint32_t a3, uint64_t descB, int scaleD, int en) {
  asm volatile("{\n.reg .pred p, e;\nsetp.ne.b32 p, %37, 0;\nsetp.ne.b32 e, %39, 0;\n"
    "@e wgmma.mma_async.sync.aligned.m64n64k16.f32.bf16.bf16 {%0, %1, %2, %3, %4, %5, %6, %7, %8, %9, %10, %11, %12, %13, %14, %15, %16, %17, %18, %19, %20, %21, %22, %23, %24, %25, %26, %27, %28, %29, %30, %31}, {%32, %33, %34, %35}, %36, p, 1, 1, %38;\n}\n"
    : "+f"(d[0]), "+f"(d[1]), "+f"(d[2]), "+f"(d[3]), "+f"(d[4]), "+f"(d[5]), "+f"(d[6]), "+f"(d[7]), "+f"(d[8]), "+f"(d[9]), "+f"(d[10]), "+f"(d[11]), "+f"(d[12]), "+f"(d[13]), "+f"(d[14]), "+f"(d[15]), "+f"(d[16]), "+f"(d[17]), "+f"(d[18]), "+f"(d[19]), "+f"(d[20]), "+f"(d[21]), "+f"(d[22]), "+f"(d[23]), "+f"(d[24]), "+f"(d[25]), "+f"(d[26]), "+f"(d[27]), "+f"(d[28]), "+f"(d[29]), "+f"(d[30]), "+f"(d[31])
    : "r"(a0), "r"(a1), "r"(a2), "r"(a3), "l"(descB), "r"(scaleD), "n"(TB), "r"(en));
}
template<int TB, int NR>
__device__ __forceinline__ void wgmma_rs_n64hi_p(float (&d)[NR], uint32_t a0, uint32_t a1, uint32_t a2, uint32_t a3, uint64_t descB, int scaleD, int en) {
  asm volatile("{\n.reg .pred p, e;\nsetp.ne.b32 p, %37, 0;\nsetp.ne.b32 e, %39, 0;\n"
    "@e wgmma.mma_async.sync.aligned.m64n64k16.f32.bf16.bf16 {%0, %1, %2, %3, %4, %5, %6, %7, %8, %9, %10, %11, %12, %13, %14, %15, %16, %17, %18, %19, %20, %21, %22, %23, %24, %25, %26, %27, %28, %29, %30, %31}, {%32, %33, %34, %35}, %36, p, 1, 1, %38;\n}\n"
    : "+f"(d[32]), "+f"(d[33]), "+f"(d[34]), "+f"(d[35]), "+f"(d[36]), "+f"(d[37]), "+f"(d[38]), "+f"(d[39]), "+f"(d[40]), "+f"(d[41]), "+f"(d[42]), "+f"(d[43]), "+f"(d[44]), "+f"(d[45]), "+f"(d[46]), "+f"(d[47]), "+f"(d[48]), "+f"(d[49]), "+f"(d[50]), "+f"(d[51]), "+f"(d[52]), "+f"(d[53]), "+f"(d[54]), "+f"(d[55]), "+f"(d[56]), "+f"(d[57]), "+f"(d[58]), "+f"(d[59]), "+f"(d[60]), "+f"(d[61]), "+f"(d[62]), "+f"(d[63])
    : "r"(a0), "r"(a1), "r"(a2), "r"(a3), "l"(descB), "r"(scaleD), "n"(TB), "r"(en));
}
template<int TB, int NR>
__device__ __forceinline__ void wgmma_rs_n64(float (&d)[NR], uint32_t a0, uint32_t a1, uint32_t a2, uint32_t a3, uint64_t descB, int scaleD) {
  asm volatile("{\n.reg .pred p;\nsetp.ne.b32 p, %37, 0;\n"
    "wgmma.mma_async.sync.aligned.m64n64k16.f32.bf16.bf16 {%0, %1, %2, %3, %4, %5, %6, %7, %8, %9, %10, %11, %12, %13, %14, %15, %16, %17, %18, %19, %20, %21, %22, %23, %24, %25, %26, %27, %28, %29, %30, %31}, {%32, %33, %34, %35}, %36, p, 1, 1, %38;\n}\n"
    : "+f"(d[0]), "+f"(d[1]), "+f"(d[2]), "+f"(d[3]), "+f"(d[4]), "+f"(d[5]), "+f"(d[6]), "+f"(d[7]), "+f"(d[8]), "+f"(d[9]), "+f"(d[10]), "+f"(d[11]), "+f"(d[12]), "+f"(d[13]), "+f"(d[14]), "+f"(d[15]), "+f"(d[16]), "+f"(d[17]), "+f"(d[18]), "+f"(d[19]), "+f"(d[20]), "+f"(d[21]), "+f"(d[22]), "+f"(d[23]), "+f"(d[24]), "+f"(d[25]), "+f"(d[26]), "+f"(d[27]), "+f"(d[28]), "+f"(d[29]), "+f"(d[30]), "+f"(d[31])
    : "r"(a0), "r"(a1), "r"(a2), "r"(a3), "l"(descB), "r"(scaleD), "n"(TB));
}
template<int TB, int NR>
__device__ __forceinline__ void wgmma_rs_n128(float (&d)[NR], uint32_t a0, uint32_t a1, uint32_t a2, uint32_t a3, uint64_t descB, int scaleD) {
  asm volatile("{\n.reg .pred p;\nsetp.ne.b32 p, %69, 0;\n"
    "wgmma.mma_async.sync.aligned.m64n128k16.f32.bf16.bf16 {%0, %1, %2, %3, %4, %5, %6, %7, %8, %9, %10, %11, %12, %13, %14, %15, %16, %17, %18, %19, %20, %21, %22, %23, %24, %25, %26, %27, %28, %29, %30, %31, %32, %33, %34, %35, %36, %37, %38, %39, %40, %41, %42, %43, %44, %45, %46, %47, %48, %49, %50, %51, %52, %53, %54, %55, %56, %57, %58, %59, %60, %61, %62, %63}, {%64, %65, %66, %67}, %68, p, 1, 1, %70;\n}\n"
    : "+f"(d[0]), "+f"(d[1]), "+f"(d[2]), "+f"(d[3]), "+f"(d[4]), "+f"(d[5]), "+f"(d[6]), "+f"(d[7]), "+f"(d[8]), "+f"(d[9]), "+f"(d[10]), "+f"(d[11]), "+f"(d[12]), "+f"(d[13]), "+f"(d[14]), "+f"(d[15]), "+f"(d[16]), "+f"(d[17]), "+f"(d[18]), "+f"(d[19]), "+f"(d[20]), "+f"(d[21]), "+f"(d[22]), "+f"(d[23]), "+f"(d[24]), "+f"(d[25]), "+f"(d[26]), "+f"(d[27]), "+f"(d[28]), "+f"(d[29]), "+f"(d[30]), "+f"(d[31]), "+f"(d[32]), "+f"(d[33]), "+f"(d[34]), "+f"(d[35]), "+f"(d[36]), "+f"(d[37]), "+f"(d[38]), "+f"(d[39]), "+f"(d[40]), "+f"(d[41]), "+f"(d[42]), "+f"(d[43]), "+f"(d[44]), "+f"(d[45]), "+f"(d[46]), "+f"(d[47]), "+f"(d[48]), "+f"(d[49]), "+f"(d[50]), "+f"(d[51]), "+f"(d[52]), "+f"(d[53]), "+f"(d[54]), "+f"(d[55]), "+f"(d[56]), "+f"(d[57]), "+f"(d[58]), "+f"(d[59]), "+f"(d[60]), "+f"(d[61]), "+f"(d[62]), "+f"(d[63])
    : "r"(a0), "r"(a1), "r"(a2), "r"(a3), "l"(descB), "r"(scaleD), "n"(TB));
}
template<int TA, int TB, int NR>
__device__ __forceinline__ void wgmma_ss_n128(float (&d)[NR], uint64_t descA, uint64_t descB, int scaleD) {
  asm volatile("{\n.reg .pred p;\nsetp.ne.b32 p, %66, 0;\n"
    "wgmma.mma_async.sync.aligned.m64n128k16.f32.bf16.bf16 {%0, %1, %2, %3, %4, %5, %6, %7, %8, %9, %10, %11, %12, %13, %14, %15, %16, %17, %18, %19, %20, %21, %22, %23, %24, %25, %26, %27, %28, %29, %30, %31, %32, %33, %34, %35, %36, %37, %38, %39, %40, %41, %42, %43, %44, %45, %46, %47, %48, %49, %50, %51, %52, %53, %54, %55, %56, %57, %58, %59, %60, %61, %62, %63}, %64, %65, p, 1, 1, %67, %68;\n}\n"
    : "+f"(d[0]), "+f"(d[1]), "+f"(d[2]), "+f"(d[3]), "+f"(d[4]), "+f"(d[5]), "+f"(d[6]), "+f"(d[7]), "+f"(d[8]), "+f"(d[9]), "+f"(d[10]), "+f"(d[11]), "+f"(d[12]), "+f"(d[13]), "+f"(d[14]), "+f"(d[15]), "+f"(d[16]), "+f"(d[17]), "+f"(d[18]), "+f"(d[19]), "+f"(d[20]), "+f"(d[21]), "+f"(d[22]), "+f"(d[23]), "+f"(d[24]), "+f"(d[25]), "+f"(d[26]), "+f"(d[27]), "+f"(d[28]), "+f"(d[29]), "+f"(d[30]), "+f"(d[31]), "+f"(d[32]), "+f"(d[33]), "+f"(d[34]), "+f"(d[35]), "+f"(d[36]), "+f"(d[37]), "+f"(d[38]), "+f"(d[39]), "+f"(d[40]), "+f"(d[41]), "+f"(d[42]), "+f"(d[43]), "+f"(d[44]), "+f"(d[45]), "+f"(d[46]), "+f"(d[47]), "+f"(d[48]), "+f"(d[49]), "+f"(d[50]), "+f"(d[51]), "+f"(d[52]), "+f"(d[53]), "+f"(d[54]), "+f"(d[55]), "+f"(d[56]), "+f"(d[57]), "+f"(d[58]), "+f"(d[59]), "+f"(d[60]), "+f"(d[61]), "+f"(d[62]), "+f"(d[63])
    : "l"(descA), "l"(descB), "r"(scaleD), "n"(TA), "n"(TB));
}
template<int TA, int TB, int NR>
__device__ __forceinline__ void wgmma_ss_n256(float (&d)[NR], uint64_t descA, uint64_t descB, int scaleD) {
  asm volatile("{\n.reg .pred p;\nsetp.ne.b32 p, %130, 0;\n"
    "wgmma.mma_async.sync.aligned.m64n256k16.f32.bf16.bf16 {%0, %1, %2, %3, %4, %5, %6, %7, %8, %9, %10, %11, %12, %13, %14, %15, %16, %17, %18, %19, %20, %21, %22, %23, %24, %25, %26, %27, %28, %29, %30, %31, %32, %33, %34, %35, %36, %37, %38, %39, %40, %41, %42, %43, %44, %45, %46, %47, %48, %49, %50, %51, %52, %53, %54, %55, %56, %57, %58, %59, %60, %61, %62, %63, %64, %65, %66, %67, %68, %69, %70, %71, %72, %73, %74, %75, %76, %77, %78, %79, %80, %81, %82, %83, %84, %85, %86, %87, %88, %89, %90, %91, %92, %93, %94, %95, %96, %97, %98, %99, %100, %101, %102, %103, %104, %105, %106, %107, %108, %109, %110, %111, %112, %113, %114, %115, %116, %117, %118, %119, %120, %121, %122, %123, %124, %125, %126, %127}, %128, %129, p, 1, 1, %131, %132;\n}\n"
    : "+f"(d[0]), "+f"(d[1]), "+f"(d[2]), "+f"(d[3]), "+f"(d[4]), "+f"(d[5]), "+f"(d[6]), "+f"(d[7]), "+f"(d[8]), "+f"(d[9]), "+f"(d[10]), "+f"(d[11]), "+f"(d[12]), "+f"(d[13]), "+f"(d[14]), "+f"(d[15]), "+f"(d[16]), "+f"(d[17]), "+f"(d[18]), "+f"(d[19]), "+f"(d[20]), "+f"(d[21]), "+f"(d[22]), "+f"(d[23]), "+f"(d[24]), "+f"(d[25]), "+f"(d[26]), "+f"(d[27]), "+f"(d[28]), "+f"(d[29]), "+f"(d[30]), "+f"(d[31]), "+f"(d[32]), "+f"(d[33]), "+f"(d[34]), "+f"(d[35]), "+f"(d[36]), "+f"(d[37]), "+f"(d[38]), "+f"(d[39]), "+f"(d[40]), "+f"(d[41]), "+f"(d[42]), "+f"(d[43]), "+f"(d[44]), "+f"(d[45]), "+f"(d[46]), "+f"(d[47]), "+f"(d[48]), "+f"(d[49]), "+f"(d[50]), "+f"(d[51]), "+f"(d[52]), "+f"(d[53]), "+f"(d[54]), "+f"(d[55]), "+f"(d[56]), "+f"(d[57]), "+f"(d[58]), "+f"(d[59]), "+f"(d[60]), "+f"(d[61]), "+f"(d[62]), "+f"(d[63]), "+f"(d[64]), "+f"(d[65]), "+f"(d[66]), "+f"(d[67]), "+f"(d[68]), "+f"(d[69]), "+f"(d[70]), "+f"(d[71]), "+f"(d[72]), "+f"(d[73]), "+f"(d[74]), "+f"(d[75]), "+f"(d[76]), "+f"(d[77]), "+f"(d[78]), "+f"(d[79]), "+f"(d[80]), "+f"(d[81]), "+f"(d[82]), "+f"(d[83]), "+f"(d[84]), "+f"(d[85]), "+f"(d[86]), "+f"(d[87]), "+f"(d[88]), "+f"(d[89]), "+f"(d[90]), "+f"(d[91]), "+f"(d[92]), "+f"(d[93]), "+f"(d[94]), "+f"(d[95]), "+f"(d[96]), "+f"(d[97]), "+f"(d[98]), "+f"(d[99]), "+f"(d[100]), "+f"(d[101]), "+f"(d[102]), "+f"(d[103]), "+f"(d[104]), "+f"(d[105]), "+f"(d[106]), "+f"(d[107]), "+f"(d[108]), "+f"(d[109]), "+f"(d[110]), "+f"(d[111]), "+f"(d[112]), "+f"(d[113]), "+f"(d[114]), "+f"(d[115]), "+f"(d[116]), "+f"(d[117]), "+f"(d[118]), "+f"(d[119]), "+f"(d[120]), "+f"(d[121]), "+f"(d[122]), "+f"(d[123]), "+f"(d[124]), "+f"(d[125]), "+f"(d[126]), "+f"(d[127])
    : "l"(descA), "l"(descB), "r"(scaleD), "n"(TA), "n"(TB));
}
template<int TB, int NR>
__device__ __forceinline__ void wgmma_rs_n256(float (&d)[NR], uint32_t a0, uint32_t a1, uint32_t a2, uint32_t a3, uint64_t descB, int scaleD) {
  asm volatile("{\n.reg .pred p;\nsetp.ne.b32 p, %133, 0;\n"
    "wgmma.mma_async.sync.aligned.m64n256k16.f32.bf16.bf16 {%0, %1, %2, %3, %4, %5, %6, %7, %8, %9, %10, %11, %12, %13, %14, %15, %16, %17, %18, %19, %20, %21, %22, %23, %24, %25, %26, %27, %28, %29, %30, %31, %32, %33, %34, %35, %36, %37, %38, %39, %40, %41, %42, %43, %44, %45, %46, %47, %48, %49, %50, %51, %52, %53, %54, %55, %56, %57, %58, %59, %60, %61, %62, %63, %64, %65, %66, %67, %68, %69, %70, %71, %72, %73, %74, %75, %76, %77, %78, %79, %80, %81, %82, %83, %84, %85, %86, %87, %88, %89, %90, %91, %92, %93, %94, %95, %96, %97, %98, %99, %100, %101, %102, %103, %104, %105, %106, %107, %108, %109, %110, %111, %112, %113, %114, %115, %116, %117, %118, %119, %120, %121, %122, %123, %124, %125, %126, %127}, {%128, %129, %130, %131}, %132, p, 1, 1, %134;\n}\n"
    : "+f"(d[0]), "+f"(d[1]), "+f"(d[2]), "+f"(d[3]), "+f"(d[4]), "+f"(d[5]), "+f"(d[6]), "+f"(d[7]), "+f"(d[8]), "+f"(d[9]), "+f"(d[10]), "+f"(d[11]), "+f"(d[12]), "+f"(d[13]), "+f"(d[14]), "+f"(d[15]), "+f"(d[16]), "+f"(d[17]), "+f"(d[18]), "+f"(d[19]), "+f"(d[20]), "+f"(d[21]), "+f"(d[22]), "+f"(d[23]), "+f"(d[24]), "+f"(d[25]), "+f"(d[26]), "+f"(d[27]), "+f"(d[28]), "+f"(d[29]), "+f"(d[30]), "+f"(d[31]), "+f"(d[32]), "+f"(d[33]), "+f"(d[34]), "+f"(d[35]), "+f"(d[36]), "+f"(d[37]), "+f"(d[38]), "+f"(d[39]), "+f"(d[40]), "+f"(d[41]), "+f"(d[42]), "+f"(d[43]), "+f"(d[44]), "+f"(d[45]), "+f"(d[46]), "+f"(d[47]), "+f"(d[48]), "+f"(d[49]), "+f"(d[50]), "+f"(d[51]), "+f"(d[52]), "+f"(d[53]), "+f"(d[54]), "+f"(d[55]), "+f"(d[56]), "+f"(d[57]), "+f"(d[58]), "+f"(d[59]), "+f"(d[60]), "+f"(d[61]), "+f"(d[62]), "+f"(d[63]), "+f"(d[64]), "+f"(d[65]), "+f"(d[66]), "+f"(d[67]), "+f"(d[68]), "+f"(d[69]), "+f"(d[70]), "+f"(d[71]), "+f"(d[72]), "+f"(d[73]), "+f"(d[74]), "+f"(d[75]), "+f"(d[76]), "+f"(d[77]), "+f"(d[78]), "+f"(d[79]), "+f"(d[80]), "+f"(d[81]), "+f"(d[82]), "+f"(d[83]), "+f"(d[84]), "+f"(d[85]), "+f"(d[86]), "+f"(d[87]), "+f"(d[88]), "+f"(d[89]), "+f"(d[90]), "+f"(d[91]), "+f"(d[92]), "+f"(d[93]), "+f"(d[94]), "+f"(d[95]), "+f"(d[96]), "+f"(d[97]), "+f"(d[98]), "+f"(d[99]), "+f"(d[100]), "+f"(d[101]), "+f"(d[102]), "+f"(d[103]), "+f"(d[104]), "+f"(d[105]), "+f"(d[106]), "+f"(d[107]), "+f"(d[108]), "+f"(d[109]), "+f"(d[110]), "+f"(d[111]), "+f"(d[112]), "+f"(d[113]), "+f"(d[114]), "+f"(d[115]), "+f"(d[116]), "+f"(d[117]), "+f"(d[118]), "+f"(d[119]), "+f"(d[120]), "+f"(d[121]), "+f"(d[122]), "+f"(d[123]), "+f"(d[124]), "+f"(d[125]), "+f"(d[126]), "+f"(d[127])
    : "r"(a0), "r"(a1), "r"(a2), "r"(a3), "l"(descB), "r"(scaleD), "n"(TB));
}

__device__ __forceinline__ void ldsm_x4(uint32_t& r0, uint32_t& r1, uint32_t& r2, uint32_t& r3, uint32_t addr) {
  asm volatile("ldmatrix.sync.aligned.m8n8.x4.shared.b16 {%0,%1,%2,%3}, [%4];"
               : "=r"(r0), "=r"(r1), "=r"(r2), "=r"(r3) : "r"(addr) : "memory");
}
__device__ __forceinline__ void mma_16816(float* d, const uint32_t* a, uint32_t b0, uint32_t b1) {
  asm volatile("mma.sync.aligned.m16n8k16.row.col.f32.bf16.bf16.f32 {%0,%1,%2,%3}, {%4,%5,%6,%7}, {%8,%9}, {%0,%1,%2,%3};"
               : "+f"(d[0]), "+f"(d[1]), "+f"(d[2]), "+f"(d[3]) : "r"(a[0]), "r"(a[1]), "r"(a[2]), "r"(a[3]), "r"(b0), "r"(b1));
}
#define RARE(c) (c)
__device__ __forceinline__ uint32_t mbar_retest(uint32_t bar, uint32_t parity) {
  uint32_t ok;
  asm volatile("{\n.reg .pred p, q;\n.reg .u32 c;\nmov.u32 c, %2;\n"
               "RL%=:\nmbarrier.test_wait.parity.shared.b64 p, [%1], %2;\nadd.u32 c, c, 1;\nsetp.lt.and.u32 q, c, 2, !p;\n@q bra RL%=;\n"
               "selp.u32 %0, 1, 0, p;\n}" : "=r"(ok) : "r"(bar), "r"(parity) : "memory");
  return ok;
}
__device__ __forceinline__ void fence_half(float (&d)[64]) {
#pragma unroll
  for (int i = 0; i < 32; i++) asm volatile("" : "+f"(d[i])::"memory");
}
#define EL(ins) "{\n.reg .pred e;\nelect.sync _|e, 0xffffffff;\n@e " ins "\n}"
__device__ __forceinline__ uint64_t policy_normal() {
  uint64_t p;
  asm volatile("createpolicy.fractional.L2::evict_normal.b64 %0, 1.0;" : "=l"(p));
  return p;
}
__device__ __forceinline__ bool elect_one() {
  uint32_t e;
  asm volatile("{\n.reg .pred e;\nelect.sync _|e, 0xffffffff;\nselp.u32 %0, 1, 0, e;\n}" : "=r"(e));
  return e;
}
__device__ __forceinline__ void e_prefetch2(const CUtensorMap* tm, int c0, int c1) {
  asm volatile(EL("cp.async.bulk.prefetch.tensor.2d.L2.global.tile [%0, {%1, %2}];") ::"l"(tm), "r"(c0), "r"(c1) : "memory");
}
__device__ __forceinline__ void e_publish(unsigned* flag) {
  asm volatile(EL("fence.proxy.async.global;\n@e red.release.gpu.global.add.u32 [%0], 1;") ::"l"(flag) : "memory");
}
__device__ __forceinline__ void e_store_tile(void* dst, uint32_t src, uint32_t empty, unsigned* flag, uint64_t pol) {
  asm volatile("{\n.reg .pred e;\n.reg .b32 ra, rb;\nmapa.shared::cluster.u32 ra, %2, 0;\nmapa.shared::cluster.u32 rb, %2, 1;\n"
               "elect.sync _|e, 0xffffffff;\n@e fence.proxy.async.shared::cta;\n"
               "@e cp.async.bulk.global.shared::cta.bulk_group.L2::cache_hint [%0], [%1], 8192, %4;\n"
               "@e cp.async.bulk.global.shared::cta.bulk_group.L2::cache_hint [%0 + 16384], [%1 + 16384], 8192, %4;\n"
               "@e cp.async.bulk.commit_group;\n@e cp.async.bulk.wait_group.read 0;\n"
               "@e mbarrier.arrive.shared::cluster.b64 _, [ra];\n@e mbarrier.arrive.shared::cluster.b64 _, [rb];\n"
               "@e cp.async.bulk.wait_group 0;\n@e fence.proxy.async.global;\n@e red.release.gpu.global.add.u32 [%3], 1;\n}"
               ::"l"(dst), "r"(src), "r"(empty), "l"(flag), "l"(pol) : "memory");
}
__device__ __forceinline__ void e_reduce2(const CUtensorMap* tm, int c0, int c1, uint32_t src) {
  asm volatile(EL("cp.reduce.async.bulk.tensor.2d.global.shared::cta.add.tile.bulk_group [%0, {%2, %3}], [%1];\n"
                  "@e cp.reduce.async.bulk.tensor.2d.global.shared::cta.add.tile.bulk_group [%0, {%5, %3}], [%4];")
               ::"l"(tm), "r"(src), "r"(c0), "r"(c1), "r"(src + ((c0 & 64) ? -HALF_B : HALF_B)), "r"(c0 ^ 64) : "memory");
}
__device__ __forceinline__ void e_expect(uint32_t bar, int bytes) {
  asm volatile(EL("mbarrier.arrive.expect_tx.shared.b64 _, [%0], %1;") ::"r"(bar), "r"(bytes) : "memory");
}
__device__ __forceinline__ void e_bulk(uint32_t dst, const void* src, int bytes, uint32_t bar) {
  asm volatile(EL("cp.async.bulk.shared::cluster.global.mbarrier::complete_tx::bytes [%0], [%1], %2, [%3];")
               ::"r"(dst), "l"(src), "r"(bytes), "r"(bar) : "memory");
}
__device__ __forceinline__ void e_bulk_mc(uint32_t dst, const void* src, int bytes, uint32_t bar) {
  asm volatile(EL("cp.async.bulk.shared::cluster.global.mbarrier::complete_tx::bytes.multicast::cluster [%0], [%1], %2, [%3], %4;")
               ::"r"(dst), "l"(src), "r"(bytes), "r"(bar), "h"((uint16_t)3) : "memory");
}
__device__ __forceinline__ void e_bulk_mc_p(uint32_t dst, const void* src, int bytes, uint32_t bar, uint64_t pol) {
  asm volatile(EL("cp.async.bulk.shared::cluster.global.mbarrier::complete_tx::bytes.multicast::cluster.L2::cache_hint [%0], [%1], %2, [%3], %4, %5;")
               ::"r"(dst), "l"(src), "r"(bytes), "r"(bar), "h"((uint16_t)3), "l"(pol) : "memory");
}
__device__ __forceinline__ void e_tma2_mc_ef(uint32_t dst, const CUtensorMap* tm, int c0, int c1, uint32_t bar, uint64_t pol) {
  asm volatile(EL("cp.async.bulk.tensor.2d.shared::cluster.global.mbarrier::complete_tx::bytes.multicast::cluster.L2::cache_hint [%0], [%1, {%3, %4}], [%2], %5, %6;")
               ::"r"(dst), "l"(tm), "r"(bar), "r"(c0), "r"(c1), "h"((uint16_t)3), "l"(pol) : "memory");
}
__device__ __forceinline__ void e_tma3_ef(uint32_t dst, const CUtensorMap* tm, int c1, int c2, uint32_t bar, uint64_t pol) {
  asm volatile(EL("cp.async.bulk.tensor.3d.shared::cluster.global.mbarrier::complete_tx::bytes.L2::cache_hint [%0], [%1, {%6, %3, %4}], [%2], %5;")
               ::"r"(dst), "l"(tm), "r"(bar), "r"(c1), "r"(c2), "l"(pol), "r"(0) : "memory");
}
__device__ __forceinline__ void e_tma5_mc(uint32_t dst, const CUtensorMap* tm, int c0, int c4, uint32_t bar) {
  asm volatile(EL("cp.async.bulk.tensor.5d.shared::cluster.global.mbarrier::complete_tx::bytes.multicast::cluster [%0], [%1, {%3, %6, %6, %6, %4}], [%2], %5;")
               ::"r"(dst), "l"(tm), "r"(bar), "r"(c0), "r"(c4), "h"((uint16_t)3), "r"(0) : "memory");
}
__device__ __forceinline__ void e_prefetch5(const CUtensorMap* tm, int c0, int c4) {
  asm volatile(EL("cp.async.bulk.prefetch.tensor.5d.L2.global.tile [%0, {%1, %3, %3, %3, %2}];") ::"l"(tm), "r"(c0), "r"(c4), "r"(0) : "memory");
}
__device__ __forceinline__ void e_prefetch(const void* p, int bytes) {
  asm volatile(EL("cp.async.bulk.prefetch.L2.global [%0], %1;") ::"l"(p), "r"(bytes) : "memory");
}
__device__ __forceinline__ void spin_ge_w(const unsigned* p, unsigned target) {
  asm volatile("{\n.reg .pred p;\n.reg .u32 c, v;\nmov.u32 c, 0;\n"
               "SL%=:\nld.acquire.gpu.global.u32 v, [%0];\nsub.u32 v, v, %1;\nsetp.ge.s32 p, v, 0;\nvote.sync.all.pred p, p, 0xffffffff;\n@p bra.uni SD%=;\n"
               "nanosleep.u32 20;\nadd.u32 c, c, 1;\nsetp.lt.u32 p, c, 0x400000;\n@p bra.uni SL%=;\ntrap;\nSD%=:\n}"
               ::"l"(p), "r"(target) : "memory");
}
__device__ __forceinline__ unsigned ld_acquire(const unsigned* p) {
  unsigned v;
  asm volatile("ld.acquire.gpu.global.u32 %0, [%1];" : "=r"(v) : "l"(p) : "memory");
  return v;
}
__device__ __forceinline__ void named_sync_dep(int id, int n, uint32_t x) {
  asm volatile("{\n.reg .pred p, q;\nsetp.ne.u32 q, %2, 0;\nbar.red.or.pred p, %0, %1, q;\n}" ::"r"(id), "r"(n), "r"(x) : "memory");
}
__device__ __forceinline__ void bulk_store(void* dst, uint32_t src, int bytes) {
  asm volatile("cp.async.bulk.global.shared::cta.bulk_group [%0], [%1], %2;" ::"l"(dst), "r"(src), "r"(bytes) : "memory");
}
__device__ __forceinline__ void fence_proxy_async_global() { asm volatile("fence.proxy.async.global;" ::: "memory"); }
__device__ __forceinline__ uint64_t desc64(uint32_t lo) { return ((uint64_t)0x40000040u << 32) | lo; }
constexpr uint32_t LBO_K = 1u << 16, LBO_16K = 1024u << 16, LBO_8K = 512u << 16;

template <int MODE>
__device__ __forceinline__ void store_image(uint8_t* tile, const float (&a)[64], uint32_t st_off, float s0, float s1, uint64_t pol) {
  uint8_t* const p0 = tile + st_off;
  uint8_t* const p1 = tile + (st_off ^ 64);
#pragma unroll
  for (int J = 0; J < 4; J++) {
#pragma unroll
    for (int rh = 0; rh < 2; rh++) {
      const float sc = rh ? s1 : s0;
      uint32_t v[4];
#pragma unroll
      for (int jj = 0; jj < 4; jj++) {
        const float lo = a[4 * (4 * J + jj) + 2 * rh], hi = a[4 * (4 * J + jj) + 2 * rh + 1];
        v[jj] = MODE == 1 ? pack_bf16(lo * sc, hi * sc) : MODE == 2 ? pack_bf16_relu(lo, hi) : pack_bf16(lo, hi);
      }
      uint8_t* p = ((J & 1) ? p1 : p0) + (J >> 1) * HALF_B + rh * 1024;
      asm volatile("st.global.L2::cache_hint.v4.b32 [%0], {%1,%2,%3,%4}, %5;" ::"l"(p), "r"(v[0]), "r"(v[1]), "r"(v[2]), "r"(v[3]), "l"(pol) : "memory");
    }
  }
}

#define NPF3 3
#define STAG 9
#define SWAPC (last || (n && j < 3))
#define OUTU 7
#define HPOL policy_ef()
#define KVPOL (t < 4 ? policy_ef() : policy_normal())
#define QPOL (t < 2 ? policy_normal() : policy_ef())
#define NO_XNPF
#define NO_OUTPF
#define STPOL policy_normal()
#define KVLPOL (LASTRD ? policy_ef() : policy_normal())
#define WPOL (helper ? policy_normal() : policy_ef())
#define LASTRD ((n == 1 ? (sp & 3) == 3 || j + 3 >= cnt : n == 2 ? j >= 8 : n == 3 && j + 3 >= cnt) && !(last && c != sw))
#define SPL 4
#define PFD 2
constexpr int SLOTS = 7, PF = PFD;
constexpr int P3_POS = 137;
constexpr int SMEM_B = SLOTS * TILE_B + 1024;
constexpr float SM_SCALE = 0.08838834764831845f * 1.4426950408889634f;

struct Ring {
  int slot; uint32_t ph;
  __device__ __forceinline__ void adv() { if (++slot == SLOTS) { slot = 0; ph ^= 1; } }
  __device__ __forceinline__ void adv(int k) { slot += k; if (slot >= SLOTS) { slot -= SLOTS; ph ^= 1; } }
};

constexpr float SM_HI = 1.8446744e19f, SM_LO = 2.3283064e-10f;
template <int J0, int J1>
__device__ __forceinline__ void mask_part(float (&s)[64], int lim) {
#pragma unroll
  for (int j = J0; j < J1; j++) {
#pragma unroll
    for (int e = 0; e < 2; e++) {
      if (8 * j + e > lim) s[4 * j + e] = -INFINITY;
      if (8 * j + e - 8 > lim) s[4 * j + 2 + e] = -INFINITY;
    }
  }
}
template <int J0, int J1>
__device__ __forceinline__ void shift_part(float (&s)[64], float b0, float b1) {
#pragma unroll
  for (int j = J0; j < J1; j++) { s[4 * j] += b0; s[4 * j + 1] += b0; s[4 * j + 2] += b1; s[4 * j + 3] += b1; }
}
template <int J0, int J1>
__device__ __forceinline__ void exp_part(float (&s)[64]) {
#pragma unroll
  for (int j = 4 * J0; j < 4 * J1; j++) s[j] = ex2(s[j]);
}
template <int J0, int J1>
__device__ __forceinline__ void sum_pack(const float (&s)[64], uint32_t (&p)[32], float& l0, float& l1) {
#pragma unroll
  for (int j = J0; j < J1; j++) {
    l0 += s[4 * j]; l1 += s[4 * j + 2]; l0 += s[4 * j + 1]; l1 += s[4 * j + 3];
    p[2 * j] = pack_bf16(s[4 * j], s[4 * j + 1]); p[2 * j + 1] = pack_bf16(s[4 * j + 2], s[4 * j + 3]);
  }
}
__device__ __forceinline__ void sum_pack_last(const float (&s)[64], uint32_t (&p)[32], float& l0, float& l1) {
#pragma unroll
  for (int j = 12; j < 16; j++) { p[2 * j] = pack_bf16(s[4 * j], s[4 * j + 1]); p[2 * j + 1] = pack_bf16(s[4 * j + 2], s[4 * j + 3]); }
  l0 += ((s[48] + s[49]) + (s[52] + s[53])) + ((s[56] + s[57]) + (s[60] + s[61]));
  l1 += ((s[50] + s[51]) + (s[54] + s[55])) + ((s[58] + s[59]) + (s[62] + s[63]));
}
__device__ __forceinline__ void ld_frag(uint32_t& r0, uint32_t& r1, uint32_t& r2, uint32_t& r3, const uint8_t* p) {
  asm volatile("ld.relaxed.gpu.global.v4.b32 {%0,%1,%2,%3}, [%4];" : "=r"(r0), "=r"(r1), "=r"(r2), "=r"(r3) : "l"(p) : "memory");
}
__device__ __forceinline__ void redo_tile(uint32_t (&p)[32], float (&o)[64], const uint8_t* qrow, const uint8_t* krow,
                                          float& b0, float& b1, float& l0, float& l1, float& t0, float& t1, int lim, float prev) {
  float4 sl[16];
  const int lane = threadIdx.x & 31;
  const int ch0 = ((lane & 3) ^ (lane >> 2)) << 4;
  krow += (lane >> 2) * 128;
#pragma unroll
  for (int c = 0; c < 4; c++) {
    ld_frag(p[8 * c], p[8 * c + 2], p[8 * c + 4], p[8 * c + 6], qrow + (c >> 1) * HALF_B + (ch0 ^ ((c & 1) << 6)));
    ld_frag(p[8 * c + 1], p[8 * c + 3], p[8 * c + 5], p[8 * c + 7], qrow + 1024 + (c >> 1) * HALF_B + (ch0 ^ ((c & 1) << 6)));
  }
  float x0 = prev, x1 = prev;
#pragma unroll 1
  for (int j = 0; j < 16; j++) {
    float s[4] = {b0, b0, b1, b1};
#pragma unroll
    for (int c = 0; c < 4; c++) {
      uint32_t k0, k1, k2, k3;
      ld_frag(k0, k1, k2, k3, krow + j * 1024 + (c >> 1) * HALF_B + (ch0 ^ ((c & 1) << 6)));
      mma_16816(s, &p[8 * c], k0, k1);
      mma_16816(s, &p[8 * c + 4], k2, k3);
    }
#pragma unroll
    for (int e = 0; e < 2; e++) {
      if (8 * j + e > lim) s[e] = -INFINITY;
      if (8 * j + e - 8 > lim) s[2 + e] = -INFINITY;
    }
    x0 = fmaxf(x0, fmaxf(s[0], s[1])); x1 = fmaxf(x1, fmaxf(s[2], s[3]));
    sl[j] = make_float4(s[0], s[1], s[2], s[3]);
  }
  x0 = fmaxf(x0, __shfl_xor_sync(0xffffffffu, x0, 1));
  x1 = fmaxf(x1, __shfl_xor_sync(0xffffffffu, x1, 1));
  x0 = fmaxf(x0, __shfl_xor_sync(0xffffffffu, x0, 2));
  x1 = fmaxf(x1, __shfl_xor_sync(0xffffffffu, x1, 2));
  const float al0 = ex2(-fmaxf(x0, 0.f)), al1 = ex2(-fmaxf(x1, 0.f));
  b0 -= x0; b1 -= x1;
  l0 *= al0; l1 *= al1;
#pragma unroll
  for (int j = 0; j < 16; j++) { o[4 * j] *= al0; o[4 * j + 1] *= al0; o[4 * j + 2] *= al1; o[4 * j + 3] *= al1; }
  t0 = 0.f; t1 = 0.f;
  uint2* const pl = reinterpret_cast<uint2*>(sl);
#pragma unroll 1
  for (int j = 0; j < 16; j++) {
    const float4 v = sl[j];
    const float e0 = ex2(v.x - x0), e1 = ex2(v.y - x0), e2 = ex2(v.z - x1), e3 = ex2(v.w - x1);
    t0 += e0 + e1; t1 += e2 + e3;
    pl[j] = make_uint2(pack_bf16(e0, e1), pack_bf16(e2, e3));
  }
#pragma unroll
  for (int j = 0; j < 16; j++) { p[2 * j] = pl[j].x; p[2 * j + 1] = pl[j].y; }
}

__device__ __forceinline__ void issue_turn(float (&s)[64], float (&o)[64], const uint32_t (&qf)[32], const uint32_t (&p)[32],
                                           uint32_t kd, uint32_t vd, int accum, int qk, int pv, int spl = 4) {
  wg_fence();
  if (qk == 2) {
#pragma unroll
    for (int kk = 0; kk < 8; kk++)
      wgmma_rs_n128<0>(s, qf[4 * kk], qf[4 * kk + 1], qf[4 * kk + 2], qf[4 * kk + 3],
                       desc64(kd + LBO_K + (kk >> 2) * 1024 + (kk & 3) * 2), kk != 0);
    wg_commit();
  } else if (qk == 1) {
#pragma unroll
    for (int kk = 0; kk < 8; kk++)
      wgmma_rs_n64<0>(s, qf[4 * kk], qf[4 * kk + 1], qf[4 * kk + 2], qf[4 * kk + 3],
                      desc64(kd + LBO_K + (kk >> 2) * 1024 + (kk & 3) * 2), kk != 0);
    wg_commit();
  }
#pragma unroll
  for (int hf = 0; hf < 2; hf++) {
    if (pv > hf) {
#pragma unroll
      for (int kk = hf ? spl : 0; kk < (hf ? 8 : spl); kk++)
        wgmma_rs_n128<1>(o, p[4 * kk], p[4 * kk + 1], p[4 * kk + 2], p[4 * kk + 3], desc64(vd + LBO_16K + kk * 128), kk != 0 ? 1 : accum);
      wg_commit();
    } else wg_commit();
  }
}

#define TS(i)
#define TR(tag)
#define TRS(tag)

enum { M_WUK, M_WUV, M_WQ, M_W1, M_W2P, M_W2, M_WO, M_WOP, M_CKV, M_OUT, M_NUM };
struct alignas(128) Maps { CUtensorMap m[M_NUM]; };

__global__ void __cluster_dims__(2, 1, 1) __launch_bounds__(384, 1)
mega(const __grid_constant__ Maps tm, const __nv_bfloat16* __restrict__ x, __nv_bfloat16* __restrict__ out) {
  extern __shared__ __align__(1024) uint8_t smem[];
  const uint32_t sbase = smem_u32(smem);
  const uint32_t bar_full = sbase + SLOTS * TILE_B, bar_empty = bar_full + 64, bar_sig = bar_full + 128;
  const int tid = threadIdx.x;
  const int rank = blockIdx.x & 1;
  const int cl = blockIdx.x >> 1;
  const bool helper = cl >= 64;
  const int sp = cl & 7, jg = cl >> 3;
  TS(0);
#define ACC(i)
#define ACC2(i)
#define ACC3(i)
#define ACCL(i)
#define ACCF()
  TR(15);
  if (tid == 0) { prefetch_tm(&tm.m[M_CKV]); prefetch_tm(&tm.m[M_WUK]); prefetch_tm(&tm.m[M_WUV]); }
  const int wid = __shfl_sync(0xffffffffu, tid >> 5, 0), wg = wid >> 2;
  if (wg == 2) reg_dec<40>();
  if (wid == 8) {
    if (elect_one()) {
#pragma unroll
      for (int i = 0; i < SLOTS; i++) { mbar_init(bar_full + 8 * i, 1); mbar_init(bar_empty + 8 * i, 4); }
      asm volatile("fence.mbarrier_init.release.cluster;\nfence.proxy.async.shared::cta;" ::: "memory");
    }
    __syncwarp();
    cluster_arrive();
    const uint64_t pol = policy_ef();
    if (!helper) {
#pragma unroll
      for (int c = 0; c < 2; c++) {
        e_expect(bar_full + 8 * c, TILE_B);
        e_tma3_ef(sbase + c * TILE_B, &tm.m[M_CKV], (sp * 2 + rank) * 128, c * 4, bar_full + 8 * c, pol);
      }
    }
    ACC3(25);
    cluster_wait();
    ACC3(26);
    if (!helper) {
#pragma unroll
      for (int kc = 0; kc < 4; kc++) {
        const int sl = kc == 3 ? 6 : 2 + kc;
        e_expect(bar_full + 8 * sl, TILE_B);
        e_tma2_mc_ef(sbase + sl * TILE_B + rank * HALF_B, &tm.m[M_WUK], (jg * 4 + 2) * 128 + rank * 64, kc * 128, bar_full + 8 * sl, pol);
      }
      e_expect(bar_full + 8 * 5, TILE_B);
      e_tma3_ef(sbase + 5 * TILE_B, &tm.m[M_CKV], (sp * 2 + rank) * 128 + 64, 0, bar_full + 8 * 5, pol);
    }
  } else {
    if (wid == 9) {
      if (elect_one()) {
#pragma unroll
        for (int i = 0; i < 16; i++) if ((i & 7) != 7) mbar_init(bar_sig + 8 * i, 4);
        asm volatile("fence.mbarrier_init.release.cluster;" ::: "memory");
      }
      __syncwarp();
    }
    cluster_arrive();
  }

  if (wg == 2) {
    auto q_src = [&](int n, int w) {
      const int i = (sp & 3) ^ ((0x3470 >> 4 * n) & 7);
      const int b = (w != (n & 1)) ? rank : 3 - rank;
      return g_q + (size_t)((jg * 4 + (sp >> 2) + (n >> 1) * 2) * NT + 2 * i + (b >> 1)) * TILE_B + (b & 1) * 8192;
    };
    const int pw = wid & 3;
    if (pw == 0) {
      Ring r{0, helper};
      const uint64_t pol = WPOL;
      unsigned epoch = 0;
      asm volatile("{\n.reg .pred p;\nsetp.eq.u32 p, %2, 256;\n@p atom.global.add.u32 %0, [%1], 1;\n}" : "+r"(epoch) : "l"(&g_flag[F_TICKET * 32]), "r"(tid) : "memory");
      auto acquire = [&](int bytes) -> uint32_t {
        mbar_wait(bar_empty + 8 * r.slot, r.ph);
        e_expect(bar_full + 8 * r.slot, bytes);
        return sbase + r.slot * TILE_B;
      };
      auto wait_flag = [&](int f, unsigned cnt) {
        spin_ge_w(&g_flag[f * 32], cnt * epoch);
        fence_proxy_async_global();
      };
      uint32_t ev0, ev1;
      {
        const int l = tid & 31;
        const int w0 = l + 4, t0 = w0 >> 2;
        ev0 = ((jg * 4 + ((t0 >> 1) ^ 2)) * 128 + rank * 64) | (w0 & 3) << 13 | (t0 & 1) << 16 | (l == 20 || l == 22) << 20;
        const int w = l < 6 ? l - 2 : l - 4, t = w >> 2;
        const int blk = helper ? 8 + t : t == 4 ? jg : jg * 4 + t;
        ev1 = (l < 2 || (l | 1) == 7) ? (l & 3) << 16 | 1 << 19
                                      : (blk * 128 + rank * 64) | (w & 3) << 13 | ((helper || t == 4) ? M_W1 : M_WQ) << 16;
        if (helper) ev0 = ev1;
      }
      if (!helper) {
        e_tma3_ef(acquire(TILE_B), &tm.m[M_CKV], (sp * 2 + rank) * 128 + 64, 4, bar_full, pol);
        r.adv();
      }
#pragma unroll 1
      for (int sg = 0; sg < (helper ? 4 : 2); sg++) {
        const int s = helper ? ((cl - 64) * 4 + sg) * 2 + rank : sp * 2 + rank;
        if (helper) {
          if (sg == 0) epoch = __shfl_sync(0xffffffffu, epoch, 0) / 132 + 1;
          wait_flag(F_LN + s, 24);
        }
        const int nev = (helper || !sg) ? 28 : 24;
#pragma unroll 1
        for (int e = 0; e < nev; e++) {
          const uint32_t w = __shfl_sync(0xffffffffu, ev0, e);
          const int m = (w >> 16) & 7;
          if (w & (1 << 19)) {
            const uint8_t* src = g_xn + (size_t)(4 * s + m) * TILE_B;
            e_bulk(acquire(TILE_B), src, TILE_B, bar_full + 8 * r.slot);
          } else {
            const CUtensorMap* map = &tm.m[m];
            const int col = w & 8191, row = (w >> 6) & 384;
            e_tma2_mc_ef(acquire(TILE_B) + rank * HALF_B, map, col, row, bar_full + 8 * r.slot, pol);
            if (w & (1 << 20)) {
              if (e == 20) e_prefetch2(&tm.m[M_WQ], (jg * 4 + (sp >> 2)) * 128 + rank * 64, (sp & 3) * 128);
              else {
                epoch = __shfl_sync(0xffffffffu, epoch, 0) / 132 + 1;
                wait_flag(F_LN + s, 24);
              }
            }
          }
          r.adv();
        }
        ev0 = ev1;
      }
      if (!helper) {
        const int s = sp * 2 + rank;
        const int split = jg >> 1, ncol = (jg & 1) * 256 + rank * 128;
        auto k64_of = [&](int u) { return u == 0 ? 14 * (split >> 1) + 6 + (split & 1) : u < 4 ? 14 * (split >> 1) + 8 * (split & 1) + 2 * u - 2 : split * 16 + (u & 1) * 2 + (u & 2) * 4 + (u & 8) / 2; };
        auto a_of = [&](int u) {
          const int k = k64_of(u);
          return u < 4 ? g_h + (size_t)(s * NFB * 2 + k) * HALF_B : g_q + (size_t)((k >> 1) * NT + s) * TILE_B;
        };
        auto map_of = [&](int u) { return &tm.m[u >= 4 ? (u >= 8 && sp < 4 ? M_WOP : M_WO) : k64_of(u) < 16 ? M_W2P : M_W2]; };
        uint64_t ev_p;
        uint32_t ev_w;
        {
          const int e = tid & 31;
          int u = 3 + (e - 7) / 3, c = (e - 7) % 3, pos = P3_POS + e;
          if (e < 7) { pos = P3_POS + ((0x5634021 >> 4 * e) & 7); u = (0x2212110 >> 4 * e) & 3; c = (0x2120011 >> 4 * e) & 3; }
          if (e >= 28) { u = 10 + ((e >> 1) & 1); c = e & 1; }
          ev_p = c == 1 ? (uint64_t)a_of(u) : (uint64_t)map_of(u);
          ev_w = (u < 10 ? ncol : ncol & 256) | (k64_of(u) + (u < 10 ? c >> 1 : rank)) << 11 | (c == 1) << 18 | (u == 4 || u == 8) << 19 | (pos % SLOTS) << 20 |
                 (~(pos / SLOTS) & 1) << 23;
        }
        TR(3);
        wait_flag(F_QA + jg, 16);
        TR(4);
        auto load_qn = [&](int n) {
          const uint32_t d = acquire(TILE_B);
#pragma unroll 1
          for (int w = 0; w < 2; w++) {
            const uint8_t* src = q_src(n, w);
            e_bulk(d + w * 8192, src, 8192, bar_full + 8 * r.slot);
            e_bulk(d + HALF_B + w * 8192, src + HALF_B, 8192, bar_full + 8 * r.slot);
          }
          r.adv();
          TR(5);
        };
        load_qn(0);
        e_bulk_mc(acquire(TILE_B) + rank * HALF_B, g_k + (size_t)(jg * 4 + (sp >> 2)) * NT * TILE_B + rank * HALF_B, HALF_B, bar_full + 8 * r.slot);
        r.adv();
        auto load_w = [&](const CUtensorMap* m, int col, int k) {
          const uint32_t d = acquire(TILE_B) + rank * HALF_B;
          e_tma5_mc(d, m, col, k, bar_full + 8 * r.slot);
          e_tma5_mc(d + 8192, m, col + 64, k, bar_full + 8 * r.slot);
        };
        bool h_ok = false;
#pragma unroll 1
        for (int n = 0; n < 4; n++) {
          const int h = jg * 4 + (sp >> 2) + (n >> 1) * 2;
          const int cnt = 2 * ((sp & 3) ^ ((0x3470 >> 4 * n) & 7)) + 2;
#pragma unroll 1
          for (int j = 0; j < cnt; j++) {
            const size_t off = (size_t)(h * NT + j) * TILE_B + rank * HALF_B;
            const bool last = j == cnt - 1;
            if (last) { if (n < 3) load_qn(n + 1); else { load_w(map_of(0), ncol, k64_of(0) * 2); r.adv(); } }
            const int sw = SWAPC;
            const Ring rv = r;
#pragma unroll 1
            for (int c = 0; c < 2; c++) {
              r = rv;
              const uint8_t* src = g_v + off;
              if (c != sw) {
                if (last && n == 3) continue;
                r.adv();
                src = g_k + off + (last ? 1 - cnt + (n & 1) * 2 * NT : 1) * TILE_B;
              }
              e_bulk_mc_p(acquire(TILE_B) + rank * HALF_B, src, HALF_B, bar_full + 8 * r.slot, KVLPOL);
            }
            r = rv;
            r.adv(last && n == 3 ? 1 : 2);
            if (n == 1 && j == 4) wait_flag(F_QB + jg, 16);
            if (n < 3) {
              if (j + PF >= cnt) {
                const size_t o2 = off + (size_t)(PF - cnt + (n & 1) * 2 * NT) * TILE_B;
                e_prefetch(g_k + o2, HALF_B);
                e_prefetch(g_v + o2, HALF_B);
              }
            } else if (j == cnt - 2) {
              h_ok = __all_sync(0xffffffffu, (int)(ld_acquire(&g_flag[(F_H + s) * 32]) - 18 * epoch) >= 0);
              fence_proxy_async_global();
#pragma unroll 1
              for (int c = 0; c < NPF3; c++) {
                const int u = (c + 1) >> 1, k = k64_of(u) + (c && !(c & 1));
                e_prefetch5(map_of(u), ncol, k * 2);
                e_prefetch5(map_of(u), ncol + 64, k * 2);
                if (h_ok) e_prefetch(g_h + (size_t)(s * NFB * 2 + k) * HALF_B, HALF_B);
              }
            }
          }
        }
        if (!h_ok) wait_flag(F_H + s, 18);
#pragma unroll 1
        for (int e = 0; e < 34; e++) {
          const int l = e < 32 ? e : 2 * e - 36;
          const uint64_t ptr = __shfl_sync(0xffffffffu, ev_p, l);
          uint32_t w = __shfl_sync(0xffffffffu, ev_w, l);
          constexpr uint32_t X0 = ((P3_POS + 28) % SLOTS ^ (P3_POS + 32) % SLOTS) << 20 | (((P3_POS + 28) / SLOTS ^ (P3_POS + 32) / SLOTS) & 1) << 23;
          constexpr uint32_t X1 = ((P3_POS + 30) % SLOTS ^ (P3_POS + 33) % SLOTS) << 20 | (((P3_POS + 30) / SLOTS ^ (P3_POS + 33) / SLOTS) & 1) << 23;
          if (e >= 32) w ^= 128 | (e == 32 ? X0 : X1);
          r.slot = (w >> 20) & 7; r.ph = w >> 23;
          if (w & (1 << 18)) {
            if (w & (1 << 19)) {
              if (elect_one()) prefetch_tm(&tm.m[M_OUT]);
              wait_flag(F_CTX + sp * 8 + split * 2 + (e >> 4), 16);
            }
            const int bytes = e ? TILE_B : HALF_B;
            e_bulk(acquire(bytes), (const void*)ptr, bytes, bar_full + 8 * r.slot);
          } else load_w((const CUtensorMap*)ptr, w & 1023, (w >> 10) & 255);
        }
      }
    } else {
      const int lane = tid & 31;
      cluster_wait();
#define LN_DELAY 2000
      if (cl & 24) __nanosleep(LN_DELAY);
      if (!helper) {
      const int hl = lane & 15;
      if (pw == 1) {
#pragma unroll
        for (int i = 0; i < 4; i++) asm volatile("prefetch.global.L2 [%0];" ::"l"(x + (size_t)blockIdx.x * 16 * DM + (i * 32 + lane) * 64));
      }
#pragma unroll 1
      for (int rr = 2 * pw - 2; rr < 16; rr += 6) {
        const int row = blockIdx.x * 16 + rr + (lane >> 4);
        const uint4* src = reinterpret_cast<const uint4*>(x + (size_t)row * DM) + hl;
        uint4* res = reinterpret_cast<uint4*>(out + (size_t)row * DM) + hl;
        uint32_t w[16];
#pragma unroll
        for (int i = 0; i < 4; i++) { const uint4 u = src[16 * i]; w[4 * i] = u.x; w[4 * i + 1] = u.y; w[4 * i + 2] = u.z; w[4 * i + 3] = u.w; }
        float sum = 0.f;
#pragma unroll
        for (int k = 0; k < 16; k++) sum += __uint_as_float(w[k] << 16) + __uint_as_float(w[k] & 0xffff0000u);
#pragma unroll
        for (int o = 8; o > 0; o >>= 1) sum += __shfl_xor_sync(0xffffffffu, sum, o);
        const float mean = sum * (1.f / DM);
        float sq = 0.f, sq1 = 0.f;
#pragma unroll
        for (int k = 0; k < 16; k++) {
          const float d0 = __uint_as_float(w[k] << (16 + blockIdx.y)) - mean, d1 = __uint_as_float(w[k] & (0xffff0000u + blockIdx.y)) - mean;
          sq = fmaf(d0, d0, sq); sq1 = fmaf(d1, d1, sq1);
        }
        sq += sq1;
#pragma unroll
        for (int o = 8; o > 0; o >>= 1) sq += __shfl_xor_sync(0xffffffffu, sq, o);
        const uint32_t mb = pack_bf16(mean, mean);
        float sd;
        asm("sqrt.approx.f32 %0, %1;" : "=f"(sd) : "f"(bf16r(bf16r(sq * (1.f / DM)) + 1e-5f)));
        const float rs = __fdividef(1.f, bf16r(sd));
        uint8_t* p = g_xn + (size_t)(row >> 6) * 65536 + (hl >> 3) * 8192 + (row & 63) * 128 + (((hl ^ row) & 7) << 4);
#pragma unroll
        for (int i = 0; i < 4; i++) {
          res[16 * i] = make_uint4(w[4 * i], w[4 * i + 1], w[4 * i + 2], w[4 * i + 3]);
          uint32_t v[4];
#pragma unroll
          for (int k = 0; k < 4; k++) {
            uint32_t d;
            asm("sub.rn.bf16x2 %0, %1, %2;" : "=r"(d) : "r"(w[4 * i + k]), "r"(mb));
            v[k] = pack_bf16(__uint_as_float(d << 16) * rs, __uint_as_float(d & 0xffff0000u) * rs);
          }
          *reinterpret_cast<uint4*>(p + i * 16384) = make_uint4(v[0], v[1], v[2], v[3]);
        }
      }
      fence_proxy_async_global();
      __syncwarp();
      if (lane == 0) red_release(&g_flag[(F_LN + (blockIdx.x >> 3)) * 32], 1);
      }
      __syncwarp();
      if (pw == 3) {
        if (!helper) {
#pragma unroll 1
          for (int e = 0; e < 2; e++) {
            mbar_wait(bar_sig + 8 * e, 0);
            mbar_wait(bar_sig + 64 + 8 * e, 0);
            e_publish(&g_flag[((e ? F_QB : F_QA) + jg) * 32]);
          }
        }
      } else {
        const uint32_t bs = bar_sig + (pw - 1) * 64;
        if (helper) {
#pragma unroll 1
          for (int e = 0; e < 4; e++) { mbar_wait(bs + 8 * e, 0); e_publish(&g_flag[(F_H + ((cl - 64) * 4 + e) * 2 + rank) * 32]); }
        } else {
          int pos = 60;
          uint8_t* dst = g_h + (size_t)((sp * 2 + rank) * NFB + jg) * TILE_B + (pw - 1) * 8192;
          unsigned* flag = &g_flag[(F_H + sp * 2 + rank) * 32];
#pragma unroll 1
          for (int n = 0; n < 4; n++) {
            const int slot = pos % SLOTS;
            mbar_wait(bs + 16 + 8 * n, 0);
            e_store_tile(dst, sbase + slot * TILE_B + (pw - 1) * 8192, bar_empty + 8 * slot, flag, STPOL);
            const int i = (sp & 3) ^ ((0x3470 >> 4 * n) & 7);
            pos += 4 * i + 4 + (n != 0);
            dst = q_src(n, pw - 1);
            flag = &g_flag[(F_CTX + i * 8 + (jg & 6) + (n >> 1)) * 32];
          }
          mbar_wait(bs + 48, 0);
          e_publish(flag);
        }
      }
    }
    __syncwarp();
    cluster_arrive();
  } else {
    reg_inc<232>();
    const int twg = tid & 127, warp = twg >> 5, lane = tid & 31, g = lane >> 2, q = lane & 3;
    const uint32_t dbase = (sbase & 0x3FFFF) >> 4;
    const int rw0 = warp * 16 + g;
    const uint32_t st_off = rw0 * 128 + ((q ^ (g & 7)) << 4);
    const int lim0 = rw0 - 2 * q;
    const uint32_t lds_off = (wg * 64 + warp * 16 + (lane & 15)) * 128 + (((lane >> 4) ^ (lane & 7)) << 4);
    const int bar_me = 4 + wg, bar_other = 4 + (wg ^ 1);
    Ring r{0, 0};
    auto release = [&](int slot) { if (twg < 2) mbar_arrive_cta(bar_empty + 8 * slot, twg); };
    auto release_n = [&](int slot, int nthr) { if (twg < nthr) mbar_arrive_cta(bar_empty + 8 * slot, twg & 1); };
    auto signal = [&](int e) {
      __syncwarp();
      if (lane == 0) mbar_arrive(bar_sig + wg * 64 + 8 * e);
    };
    if (wg == 1) named_arrive(4, 256);
    cluster_wait();

    float acc[64];
    {
      uint32_t a[128];
      const int nseg = helper ? 4 : 2;
      Ring ra{0, 0};
      auto read_a = [&](int c) {
        mbar_wait(bar_full + 8 * ra.slot, ra.ph);
        const uint32_t ad = sbase + ra.slot * TILE_B - wg * 8192;
        uint32_t lo = lds_off;
        asm volatile("" : "+r"(lo));
#pragma unroll
        for (int kk = 0; kk < 16; kk++)
          ldsm_x4(a[c * 64 + kk * 4], a[c * 64 + kk * 4 + 1], a[c * 64 + kk * 4 + 2], a[c * 64 + kk * 4 + 3],
                  ad + (kk >> 2) * 8192 + (lo ^ ((kk & 3) << 5)));
      };
      auto free_a = [&](int c) {
        uint32_t dep = 0;
#pragma unroll
        for (int kk = 0; kk < 16; kk++) dep |= a[c * 64 + kk * 4];
        named_sync_dep(2 + wg, 128, dep);
        release_n(ra.slot, 4);
      };
      for (int sg = 0; sg < nseg; sg++) {
        const int xn = helper || sg;
        if (wg | !sg) { ra = r; ra.adv(wg * (5 + xn)); read_a(0); }
        free_a(0);
        ra.adv(xn ? 1 : 1 + wg);
        r.adv(2);
        if (sg == 0) TS(1);
        ACC2(sg);
        const int s = helper ? ((cl - 64) * 4 + sg) * 2 + rank : sp * 2 + rank;
        const int ntile = helper ? 6 : (sg ? 5 : 8);
        for (int t = 0; t < ntile; t++) {
          int prev = 0;
          TR(0);
          mbar_wait(bar_full + 8 * r.slot, r.ph);
          named_sync(bar_me, 256);
#pragma unroll
          for (int kc = 0; kc < 4; kc++) {
            if (kc > 0) mbar_wait(bar_full + 8 * r.slot, r.ph);
            if (kc == 1 && t == 0) read_a(1);
            const uint32_t bd = dbase + r.slot * 2048 + LBO_16K;
            wg_fence();
#pragma unroll
            for (int kk = 0; kk < 8; kk++)
              wgmma_rs_n128<1>(acc, a[kc * 32 + kk * 4], a[kc * 32 + kk * 4 + 1], a[kc * 32 + kk * 4 + 2], a[kc * 32 + kk * 4 + 3],
                               desc64(bd + kk * 128), (kc | kk) != 0);
            wg_commit();
            if (kc == 3 && !(helper && wg == 1 && sg == 3 && t == 5)) named_arrive(bar_other, 256);
            if (kc > 0) { wg_wait<1>(); release(prev); }
            if (kc == 1 && t == 0) free_a(1);
            prev = r.slot;
            if (kc >= 2) r.adv(t == 0 ? 2 + (2 * kc - 5) * xn : 1); else r.adv();
          }
          const bool turn = t == ntile - 1 && sg != nseg - 1;
          if (turn && wg == 0) { ra = r; read_a(0); }
          wg_wait<0>();
          fence_regs(acc);
          TR(4);
          ACC2(2 + sg * 8 + t);
          release(prev);
          if (helper)
            store_image<2>(g_h + (size_t)(s * NFB + 8 + t) * TILE_B + wg * 8192, acc, st_off, 0.f, 0.f, HPOL);
          else if (sg == 0)
            store_image<0>(((t & 1) ? g_v : g_k) + (size_t)((jg * 4 + ((t >> 1) ^ 2)) * NT + s) * TILE_B + wg * 8192, acc, st_off, 0.f, 0.f, KVPOL);
          else if (t < 4) {
            store_image<1>(g_q + (size_t)((jg * 4 + t) * NT + s) * TILE_B + wg * 8192, acc, st_off, SM_SCALE, SM_SCALE, QPOL);
            if (t & 1) signal(t >> 1);
          }
        }
        if (helper) signal(sg);
      }
    }
    TS(2);
    ACC(0);
    ACC2(15);
    if (!helper) {
      float o[64], fl0, fl1;
      uint8_t* ctx_last;
      {
        uint32_t p[32], qf[32];
        float l0 = 0.25f, l1 = 0.25f, b0, b1;
        int vslot = 0, accum = 0, nrel = 0, pv = 0, qslot;
        auto inv_sum = [&](float l) {
          l += __shfl_xor_sync(0xffffffffu, l, 1);
          l += __shfl_xor_sync(0xffffffffu, l, 2);
          return __fdividef(1.f, l);
        };
        auto wait_q = [&](int back) {
          qslot = r.slot - back;
          uint32_t ph = r.ph;
          if (qslot < 0) { qslot += SLOTS; ph ^= 1; }
          mbar_wait(bar_full + 8 * qslot, ph);
        };
        auto test_q = [&]() {
          qslot = r.slot - 2;
          uint32_t ph = r.ph;
          if (qslot < 0) { qslot += SLOTS; ph ^= 1; }
          return mbar_retest(bar_full + 8 * qslot, ph);
        };
        auto load_q = [&]() {
          const uint32_t ad = sbase + qslot * TILE_B;
          uint32_t lo = lds_off;
          asm volatile("" : "+r"(lo));
#pragma unroll
          for (int kk = 0; kk < 8; kk++)
            ldsm_x4(qf[4 * kk], qf[4 * kk + 1], qf[4 * kk + 2], qf[4 * kk + 3], ad + (kk >> 2) * HALF_B + (lo ^ ((kk & 3) << 5)));
        };
        auto stage = [&](int slot, float f0, float f1) {
          const uint32_t ad = sbase + slot * TILE_B;
          uint32_t lo = lds_off;
          asm volatile("" : "+r"(lo));
#pragma unroll
          for (int kk = 0; kk < 8; kk++)
            stsm_x4(ad + (kk >> 2) * HALF_B + (lo ^ ((kk & 3) << 5)), pack_bf16(o[8 * kk] * f0, o[8 * kk + 1] * f0),
                    pack_bf16(o[8 * kk + 2] * f1, o[8 * kk + 3] * f1), pack_bf16(o[8 * kk + 4] * f0, o[8 * kk + 5] * f0),
                    pack_bf16(o[8 * kk + 6] * f1, o[8 * kk + 7] * f1));
        };
        int b = wg ? rank : 3 - rank;
        int left0 = 2 * (sp & 3) + (b >> 1);
        auto redo = [&](int n, int left, float& x0, float& x1, float& t0, float& t1, float prev) {
          const size_t off = (size_t)((jg * 4 + (sp >> 2) + (n >> 1) * 2) * NT + left0) * TILE_B;
          redo_tile(p, o, g_q + off + ((b & 1) * 64 + rw0) * 128, g_k + off - left * TILE_B, b0, b1, x0, x1, t0, t1,
                    left ? 1000 : (b & 1) * 64 + lim0, prev);
        };
        TR(7);
        r.adv();
        wait_q(1);
        load_q();
#pragma unroll
        for (int c = 0; c < 32; c++) asm volatile("" : "=r"(p[c]));
#pragma unroll
        for (int c = 0; c < 64; c++) o[c] = fmaxf(acc[c], 0.f);
        mbar_wait(bar_full + 8 * r.slot, r.ph);
        for (int n = 0; n < 4; n++) {
          int left = left0;
          bool use_b;
          uint32_t okq = 0;
          {
            float s[64];
            TR(8);
            named_sync(bar_me, 256);
            TR(9);
            if (n == 0) ACC2(16);
            issue_turn(s, o, qf, p, dbase + r.slot * 2048, dbase + vslot * 2048, accum, 2, pv);
            named_arrive(bar_other, 256);
            const int kslot = r.slot, vprev = vslot, qs = qslot;
            r.adv();
            const uint32_t vbar = bar_full + 8 * r.slot, vph = r.ph;
            uint32_t okv = mbar_test(vbar, vph);
            vslot = r.slot; r.adv(left ? 1 : 4);
            uint32_t okk = mbar_test(bar_full + 8 * r.slot, r.ph);
            const float fl0 = inv_sum(l0), fl1 = inv_sum(l1);
            if (RARE(left == 0)) okq = test_q();
            wg_wait<2>();
            fence_regs(s);
            if (RARE(left == 0)) { load_q(); mask_part<0, 16>(s, (b & 1) * 64 + lim0); }
            exp_part<0, 6>(s);
            fence_regs(s);
            if (RARE(!okv)) okv = mbar_retest(vbar, vph);
            wg_wait<1>();
            release(kslot);
            l0 = 0.f; l1 = 0.f;
            exp_part<6, 10>(s);
            sum_pack<0, 6>(s, p, l0, l1);
            fence_regs(s);
            fence_regs(p);
            if (RARE(!okk)) okk = mbar_retest(bar_full + 8 * r.slot, r.ph);
            wg_wait<0>();
            fence_regs(o);
            release_n(vprev, nrel);
            exp_part<10, 16>(s);
            stage(qs, fl0, fl1);
            sum_pack<6, 12>(s, p, l0, l1);
            sum_pack_last(s, p, l0, l1);
            uint32_t m0 = __ballot_sync(0xffffffffu, l0 > SM_LO), m1 = __ballot_sync(0xffffffffu, l1 > SM_LO);
            use_b = __any_sync(0xffffffffu, !(fmaxf(l0, l1) < SM_HI));
            signal(2 + n);
            m0 |= m0 >> 1; m1 |= m1 >> 1;
            use_b |= (((m0 | m0 >> 2) & (m1 | m1 >> 2)) | 0xeeeeeeeeu) != 0xffffffffu;
            b0 = 0.f; b1 = 0.f;
            if (RARE(use_b)) { float x0 = 0.f, x1 = 0.f; redo(n, left, x0, x1, l0, l1, -INFINITY); }
            if (RARE(!(okv & okk))) {
              mbar_wait(vbar, vph);
              if (left || n < 3) mbar_wait(bar_full + 8 * r.slot, r.ph);
            }
            TR(4);
          }
          accum = 0;
          while (left > (~b & 1)) {
            left--;
            TR(5);
            float t0 = 0.f, t1 = 0.f;
            float s[64];
            named_sync(bar_me, 256);
            issue_turn(s, o, qf, p, dbase + r.slot * 2048, dbase + vslot * 2048, accum, 2, 2, SPL);
            named_arrive(bar_other, 256);
            const int kslot = r.slot, vprev = vslot;
            r.adv(left ? 1 : 1 + (b >> 1));
            const uint32_t vbar = bar_full + 8 * r.slot, vph = r.ph;
            uint32_t okv = mbar_test(vbar, vph);
            vslot = r.slot; r.adv((left | (b >> 1)) ? 1 : 4);
            uint32_t okk = mbar_test(bar_full + 8 * r.slot, r.ph);
            if (RARE(left == 0)) okq = test_q();
            wg_wait<2>();
            fence_regs(s);
            if (RARE(use_b)) shift_part<0, 16>(s, b0, b1);
            if (RARE(left == 0)) {
              if (b >> 1) release(kslot);
              load_q();
              mask_part<8, 16>(s, 64 + lim0);
              exp_part<0, 7>(s);
              fence_regs(s);
            } else {
              exp_part<0, 7>(s);
              fence_regs(s);
            }
            if (RARE(!okv)) okv = mbar_retest(vbar, vph);
            wg_wait<1>();
            release(kslot);
            exp_part<7, 11>(s);
            sum_pack<0, 6>(s, p, t0, t1);
            fence_regs(s);
            fence_regs(p);
            if (RARE(!okk)) okk = mbar_retest(bar_full + 8 * r.slot, r.ph);
            wg_wait<0>();
            fence_regs(o);
            release(vprev);
            exp_part<11, 16>(s);
            sum_pack<6, 12>(s, p, t0, t1);
            fence_regs(s);
            fence_regs(p);
            if (RARE(!(okv & okk))) {
              mbar_wait(vbar, vph);
              if (left || n < 3) mbar_wait(bar_full + 8 * r.slot, r.ph);
            }
            sum_pack_last(s, p, t0, t1);
            accum = 1;
            if (RARE(__any_sync(0xffffffffu, !(fmaxf(t0, t1) < SM_HI)))) {
              redo(n, left, l0, l1, t0, t1, 0.f);
              use_b = true;
            }
            l0 += t0; l1 += t1;
          }
          if (left) {
            TR(5);
            float t0 = 0.f, t1 = 0.f;
            float s[64];
            named_sync(bar_me, 256);
            issue_turn(s, o, qf, p, dbase + r.slot * 2048, dbase + vslot * 2048, accum, 1, 2);
            named_arrive(bar_other, 256);
            const int kslot = r.slot, vprev = vslot;
            r.adv(1 + (b >> 1));
            const uint32_t vbar = bar_full + 8 * r.slot, vph = r.ph;
            vslot = r.slot; r.adv((b >> 1) ? 1 : 4);
            okq = test_q();
            wg_wait<2>();
            fence_half(s);
            release_n(kslot, 2 + (b & 2));
            if (RARE(use_b)) shift_part<0, 8>(s, b0, b1);
            load_q();
            mask_part<0, 8>(s, lim0);
            exp_part<0, 8>(s);
            fence_half(s);
            mbar_wait(vbar, vph);
            wg_wait<1>();
            sum_pack<0, 8>(s, p, t0, t1);
            fence_regs(p);
            if (n < 3) mbar_wait(bar_full + 8 * r.slot, r.ph);
            wg_wait<0>();
            fence_regs(o);
            release(vprev);
            accum = 1;
            if (RARE(__any_sync(0xffffffffu, !(fmaxf(t0, t1) < SM_HI)))) redo(n, 0, l0, l1, t0, t1, 0.f);
            l0 += t0; l1 += t1;
          }
          if (RARE(!okq && n < 3)) { wait_q(2); load_q(); }
          TR(6);
          ACC2(17 + n);
          nrel = 2 + (b & 2);
          pv = 1 + (b & 1);
          b ^= 3;
          left0 ^= n == 1 ? 7 : 15;
        }
        named_sync(bar_me, 256);
        issue_turn(o, o, qf, p, 0, dbase + vslot * 2048, accum, 0, pv);
        if (wg == 0) named_arrive(bar_other, 256);
        fl0 = inv_sum(l0); fl1 = inv_sum(l1);
        ctx_last = g_q + (size_t)((jg * 4 + (sp >> 2) + 2) * NT + 15 - left0) * TILE_B + (~b & 1) * 8192;
        wg_wait<0>();
        fence_regs(o);
        release_n(vslot, nrel);
      }
      TS(3);
      ACC(1);
      ACC2(21);
      TR(10);
      {
        float acc[128];
        const int nh = jg & 1, st = sp * 2 + rank;
        const uint32_t aoff = LBO_K + wg * 512;
        auto next = [&]() { mbar_wait(bar_full + 8 * r.slot, r.ph); const int sl = r.slot; r.adv(); return sl; };
        r.adv(5); r.ph ^= 1;
        int pb = next();
        r.adv(2);
        int pa = next();
        r.adv(5); r.ph ^= 1;
        wg_fence();
#pragma unroll
        for (int kk = 0; kk < 4; kk++)
          wgmma_ss_n256<0, 1>(acc, desc64(dbase + pa * 2048 + aoff + kk * 2), desc64(dbase + pb * 2048 + LBO_8K + kk * 128), kk != 0);
        wg_commit();
#pragma unroll 1
        for (int t = 0; t < 9; t++) {
          const int sb0 = next();
          if (t < 2) r.adv();
          const int sa = next();
          wg_fence();
#pragma unroll
          for (int kk = 0; kk < 4; kk++)
            wgmma_ss_n256<0, 1>(acc, desc64(dbase + sa * 2048 + aoff + kk * 2), desc64(dbase + sb0 * 2048 + LBO_8K + kk * 128), 1);
          wg_commit();
          if (t == 0) {
            store_image<1>(ctx_last, o, st_off, fl0, fl1, policy_normal());
            signal(6);
          }
          wg_wait<1>();
          release(pa); release(pb);
          if (t == 1) { r.adv(5); r.ph ^= 1; }
          const int sb1 = next();
          if (t == 1) r.adv();
          wg_fence();
#pragma unroll
          for (int kk = 0; kk < 4; kk++)
            wgmma_ss_n256<0, 1>(acc, desc64(dbase + sa * 2048 + 1024 + aoff + kk * 2), desc64(dbase + sb1 * 2048 + LBO_8K + kk * 128), 1);
          wg_commit();
          wg_wait<1>();
          release(sb0);
          pa = sa; pb = sb1;
        }
        const int srow = warp * 16 + (lane & 7) + (lane & 8);
        auto flush = [&](const float* d, uint32_t sb, int stride, int col) {
#pragma unroll
          for (int c = 0; c < 2; c++) {
#pragma unroll
            for (int jj = 0; jj < 4; jj++) {
              const int j = c * 8 + jj * 2;
              stsm_x4(sb + c * stride + srow * 128 + (((2 * jj + (lane >> 4)) ^ (lane & 7)) << 4), pack_bf16(d[4 * j], d[4 * j + 1]),
                      pack_bf16(d[4 * j + 2], d[4 * j + 3]), pack_bf16(d[4 * j + 4], d[4 * j + 5]), pack_bf16(d[4 * j + 6], d[4 * j + 7]));
            }
          }
          asm volatile("fence.proxy.async.shared::cta;" ::: "memory");
          __syncwarp();
          const int c = (jg >> 1) & 1;
          e_reduce2(&tm.m[M_OUT], nh * 256 + col + c * 64, st * 128 + (wid & 7) * 16, sb + c * HALF_B + (wid & 3) * 2048);
        };
#define FIRSTWG 1
        const bool first = wg == FIRSTWG;
        float lo[64], hi[64];
        uint32_t af[64];
        auto read_a = [&](int c, int slot) {
          uint32_t lo = lds_off;
          asm volatile("" : "+r"(lo));
#pragma unroll
          for (int kk = 0; kk < 8; kk++)
            ldsm_x4(af[c * 32 + 4 * kk], af[c * 32 + 4 * kk + 1], af[c * 32 + 4 * kk + 2], af[c * 32 + 4 * kk + 3],
                    sbase + slot * TILE_B + (kk >> 2) * HALF_B + (lo ^ ((kk & 3) << 5)));
        };
        auto half = [&](float (&d)[64], int c, int sb) {
          wg_fence();
#pragma unroll
          for (int kk = 0; kk < 8; kk++)
            wgmma_rs_n128<1>(d, af[c * 32 + 4 * kk], af[c * 32 + 4 * kk + 1], af[c * 32 + 4 * kk + 2], af[c * 32 + 4 * kk + 3],
                             desc64(dbase + sb * 2048 + LBO_8K + (kk >> 2) * 1024 + (kk & 3) * 128), 1);
        };
        const int l9 = next(), a9 = next();
        wg_wait<0>();
        fence_regs(acc);
        ACCL(0);
        release(pa);
        cluster_arrive();
        const float z = __int_as_float(blockIdx.y);
#pragma unroll
        for (int i = 0; i < 64; i++) lo[i] = acc[i] + z;
        fence_regs(lo);
        if (!first) named_sync(bar_me, 256);
        ACCL(1);
        wg_fence();
#pragma unroll
        for (int kk = 0; kk < 8; kk++)
          wgmma_ss_n128<0, 1>(lo, desc64(dbase + a9 * 2048 + aoff + (kk >> 2) * 1024 + (kk & 3) * 2),
                              desc64(dbase + l9 * 2048 + LBO_8K + (kk >> 2) * 1024 + (kk & 3) * 128), 1);
#pragma unroll
        for (int i = 0; i < 64; i++) hi[i] = acc[64 + i] + z;
        fence_regs(hi);
        const int l10 = next(), a10 = next();
        read_a(1, a10);
        half(lo, 1, l10);
        wg_commit();
        named_arrive(bar_other, 256);
        read_a(0, a9);
        wg_wait<0>();
        fence_regs(lo);
        ACCL(2);
        flush(lo, sbase + a9 * TILE_B + wg * 8192, HALF_B, 0);
        ACCL(3);
        const int h9 = next(), h10 = next();
        named_sync(bar_me, 256);
        ACCL(4);
        half(hi, 0, h9);
        half(hi, 1, h10);
        wg_commit();
        if (first) named_arrive(bar_other, 256);
        wg_wait<0>();
        fence_regs(hi);
        ACCL(5);
        flush(hi, sbase + a10 * TILE_B + wg * 8192, HALF_B, 128);
        asm volatile("cp.async.bulk.commit_group;\ncp.async.bulk.wait_group.read 0;" ::: "memory");
        __syncwarp();
      }
    }
    else cluster_arrive();
    TS(6);
    ACC(2);
    ACC2(23);
    if (!helper) ACCF();
    TR(13);
    cluster_wait();
  }
}

typedef CUresult (*EncodeFn)(CUtensorMap*, CUtensorMapDataType, cuuint32_t, void*, const cuuint64_t*, const cuuint64_t*,
                             const cuuint32_t*, const cuuint32_t*, CUtensorMapInterleave, CUtensorMapSwizzle,
                             CUtensorMapL2promotion, CUtensorMapFloatOOBfill);

void make_map(EncodeFn enc, CUtensorMap* tm, const void* ptr, int cols, int rows, int box_rows) {
  cuuint64_t dims[2] = {(cuuint64_t)cols, (cuuint64_t)rows};
  cuuint64_t strides[1] = {(cuuint64_t)cols * 2};
  cuuint32_t box[2] = {64, (cuuint32_t)box_rows};
  cuuint32_t es[2] = {1, 1};
  enc(tm, CU_TENSOR_MAP_DATA_TYPE_BFLOAT16, 2, const_cast<void*>(ptr), dims, strides, box, es, CU_TENSOR_MAP_INTERLEAVE_NONE,
      CU_TENSOR_MAP_SWIZZLE_128B, CU_TENSOR_MAP_L2_PROMOTION_L2_128B, CU_TENSOR_MAP_FLOAT_OOB_FILL_NONE);
}
void make_map_act(EncodeFn enc, CUtensorMap* tm, const void* ptr) {
  cuuint64_t dims[3] = {64, SEQ, DM / 64};
  cuuint64_t strides[2] = {DM * 2, 128};
  cuuint32_t box[3] = {64, 64, 4};
  cuuint32_t es[3] = {1, 1, 1};
  enc(tm, CU_TENSOR_MAP_DATA_TYPE_BFLOAT16, 3, const_cast<void*>(ptr), dims, strides, box, es, CU_TENSOR_MAP_INTERLEAVE_NONE,
      CU_TENSOR_MAP_SWIZZLE_128B, CU_TENSOR_MAP_L2_PROMOTION_L2_128B, CU_TENSOR_MAP_FLOAT_OOB_FILL_NONE);
}
void make_map_w2(EncodeFn enc, CUtensorMap* tm, const void* ptr, int rows, bool perm) {
  const cuuint64_t R = DM * 2;
  cuuint64_t dims[5] = {DM, 2, 4, 4, (cuuint64_t)rows / 32};
  cuuint64_t strides[4] = {R, (perm ? 8 : 2) * R, (perm ? 2 : 8) * R, 32 * R};
  cuuint32_t box[5] = {64, 2, 4, 4, 2};
  cuuint32_t es[5] = {1, 1, 1, 1, 1};
  enc(tm, CU_TENSOR_MAP_DATA_TYPE_BFLOAT16, 5, const_cast<void*>(ptr), dims, strides, box, es, CU_TENSOR_MAP_INTERLEAVE_NONE,
      CU_TENSOR_MAP_SWIZZLE_128B, CU_TENSOR_MAP_L2_PROMOTION_L2_128B, CU_TENSOR_MAP_FLOAT_OOB_FILL_NONE);
}

}

extern "C" void kernel_launch(void* const* d_in, const int* in_sizes, int n_in, void* d_out, int out_size) {
  static EncodeFn enc = nullptr;
  if (!enc) {
    void* fn = nullptr; cudaDriverEntryPointQueryResult qr;
    cudaGetDriverEntryPoint("cuTensorMapEncodeTiled", &fn, cudaEnableDefault, &qr);
    enc = (EncodeFn)fn;
    cudaFuncSetAttribute(mega, cudaFuncAttributeMaxDynamicSharedMemorySize, SMEM_B);
  }
  Maps tm;
  make_map_act(enc, &tm.m[M_CKV], d_in[1]);
  make_map(enc, &tm.m[M_WQ], d_in[2], 4096, DM, 128);
  make_map(enc, &tm.m[M_WUK], d_in[3], 4096, DM, 128);
  make_map(enc, &tm.m[M_WUV], d_in[4], 4096, DM, 128);
  make_map_w2(enc, &tm.m[M_WO], d_in[5], 4096, true);
  make_map_w2(enc, &tm.m[M_WOP], d_in[5], 4096, false);
  make_map(enc, &tm.m[M_W1], d_in[7], DFF, DM, 128);
  make_map_w2(enc, &tm.m[M_W2], d_in[8], DFF, true);
  make_map_w2(enc, &tm.m[M_W2P], d_in[8], DFF, false);
  make_map(enc, &tm.m[M_OUT], d_out, DM, SEQ, 16);
  mega<<<132, 384, SMEM_B>>>(tm, (const __nv_bfloat16*)d_in[0], (__nv_bfloat16*)d_out);
}
```
